```python
import torch

def _softmax(x, axis=-1):
    return torch.softmax(x, dim=axis)
def _gelu(x):
    return torch.nn.functional.gelu(x, approximate="tanh")
def _silu(x):
    return torch.nn.functional.silu(x)
def _sigmoid(x):
    return torch.sigmoid(x)
def _layernorm(x, axis=-1, eps=1e-5):
    m = x.mean(dim=axis, keepdim=True)
    v = x.var(dim=axis, keepdim=True, unbiased=False)
    return (x - m) / torch.sqrt(v + eps)
def _scatter_add(tgt, idx, src, axis=0):
    return tgt.clone().index_add_(axis, idx, src)
def _segment_sum(src, seg, n):
    out = torch.zeros((n,) + src.shape[1:], dtype=src.dtype)
    return out.index_add_(0, seg, src)
def _pad(x, pw):
    flat = tuple(v for pair in reversed(pw) for v in pair)
    return torch.nn.functional.pad(x, flat)

kernel_name = 'interleave_layers__sliding_local_dilated__glu_gated_bilinear__prompt'

def setup_inputs():

    _w = (lambda a: (lambda t: t.to(torch.bfloat16) if t.is_floating_point() else t)(torch.as_tensor(a)))
    def _A_setup():
        B, S, D = 1, 2048, 512
        return {
            "x": _w((lambda *s: torch.randn(*s, dtype=torch.bfloat16) * 0.05)(B, S, D)),
            "wqkv": _w((lambda *s: torch.randn(*s, dtype=torch.bfloat16) * 0.05)(D, 3 * D)),
            "wo": _w((lambda *s: torch.randn(*s, dtype=torch.bfloat16) * 0.05)(D, D)),
        }
    _A_in = _A_setup()

    def _B_setup():
        B, S, D, F = 1, 2048, 512, 1792
        return {
            "x": _w((lambda *s: torch.randn(*s, dtype=torch.bfloat16) * 0.05)(B, S, D)),
            "w_gate": _w((lambda *s: torch.randn(*s, dtype=torch.bfloat16) * 0.8)(D, F) * (D ** -0.5)),
            "w_up": _w((lambda *s: torch.randn(*s, dtype=torch.bfloat16) * 0.8)(D, F) * (D ** -0.5)),
            "w_down": _w((lambda *s: torch.randn(*s, dtype=torch.bfloat16) * 0.8)(F, D) * (F ** -0.5)),
        }
    _B_in = _B_setup()

    return {
        "A_x": _A_in["x"],
        "A_wqkv": _A_in["wqkv"],
        "A_wo": _A_in["wo"],
        "B_x": _B_in["x"],
        "B_w_gate": _B_in["w_gate"],
        "B_w_up": _B_in["w_up"],
        "B_w_down": _B_in["w_down"],
    }

def reference(A_x, A_wqkv, A_wo, B_x, B_w_gate, B_w_up, B_w_down):
    def _A_ref(x, wqkv, wo):
        B, S, D = x.shape
        H = 32; Dh = D // H
        W, dil = 8, 2
        qkv = (lambda x, *d: x.permute(*d))((x @ wqkv).reshape(B, S, 3, H, Dh), 2, 0, 3, 1, 4)
        q, k, v = qkv[0], qkv[1], qkv[2]
        scale = Dh ** -0.5
        pos = torch.arange(S)
        off = torch.arange(W) * dil
        idx = pos[:, None] - off[None, :]
        mask = idx >= 0
        idx_c = torch.where(mask, idx, 0).reshape(-1)
        kg = k[:, :, idx_c, :].reshape(B, H, S, W, Dh)
        vg = v[:, :, idx_c, :].reshape(B, H, S, W, Dh)
        logits = torch.einsum("bhsd,bhswd->bhsw", q, kg) * scale
        logits = torch.where(mask[None, None, :, :], logits, -1e9)
        attn = _softmax(logits, axis=-1)
        o = torch.einsum("bhsw,bhswd->bhsd", attn, vg)
        return (lambda x, *d: x.permute(*d))(o, 0, 2, 1, 3).reshape(B, S, D) @ wo

    def _B_ref(x, w_gate, w_up, w_down):
        g = torch.einsum("bsd,df->bsf", x, w_gate)
        u = torch.einsum("bsd,df->bsf", x, w_up)
        h = g * u
        return torch.einsum("bsf,fd->bsd", h, w_down)

    x = A_x
    x = x + _A_ref(_layernorm(x, axis=-1), A_wqkv, A_wo)
    x = x + _B_ref(_layernorm(x, axis=-1), B_w_gate, B_w_up, B_w_down)
    x = x + _A_ref(_layernorm(x, axis=-1), A_wqkv, A_wo)
    x = x + _B_ref(_layernorm(x, axis=-1), B_w_gate, B_w_up, B_w_down)
    return x
```

```cpp
#include <cuda_runtime.h>
#include <cuda_bf16.h>
#include <cuda.h>
#include <stdint.h>

namespace {

constexpr int S_LEN = 2048, DM = 512, FF = 1792;
constexpr int NT = 32;
constexpr int NST = 12;
constexpr int STAGE_BYTES = 16384;
constexpr int KV_BYTES = 16384;
constexpr int SM_RING = 0;
constexpr int SM_KV = NST * STAGE_BYTES;
constexpr int SM_BAR = SM_KV + 2 * KV_BYTES;
constexpr int SM_TOTAL = SM_BAR + 256;
constexpr int NTHREADS = 384;
constexpr int NCLUSTERS = 64;
constexpr int STAGES_PER_LAYER = 12 + 4 + 28 + 14;
constexpr unsigned SPIN_LIMIT = 1u << 22;

__device__ uint4 g_o[NT * 32 * 128];
__device__ uint4 g_x1[NT * 32 * 128];
__device__ uint4 g_x2[NT * 32 * 128];
__device__ uint4 g_h[NT * 112 * 128];
__device__ float4 g_st1[NT * 4 * 8 * 8];
__device__ float4 g_st2[NT * 4 * 8 * 8];
__device__ uint4 g_halo[2 * NT * 8 * 2 * 4 * 32];
constexpr int FLAG_STRIDE = 16;
constexpr int FL_O = 0, FL_X1 = 128, FL_H = 256, FL_X2 = 384, FL_HALO = 512;
constexpr int N_FLAGS = 768;
__device__ unsigned g_flag[N_FLAGS * FLAG_STRIDE];
__device__ unsigned long long g_ticket;
__device__ unsigned g_done;

struct Params {
    CUtensorMap tm_x;
    CUtensorMap tm_qkv;
    CUtensorMap tm_wo;
    CUtensorMap tm_wg;
    CUtensorMap tm_wu;
    CUtensorMap tm_wd;
    const __nv_bfloat16* x;
    __nv_bfloat16* out;
    unsigned char gpc_of_tpc[80];
};

__device__ __forceinline__ uint32_t smem_u32(const void* p) { return (uint32_t)__cvta_generic_to_shared(p); }
__device__ __forceinline__ uint32_t opaque(uint32_t x) { uint32_t y; asm volatile("mov.u32 %0, %1;" : "=r"(y) : "r"(x)); return y; }
__device__ __forceinline__ bool elect_one() {
    uint32_t p;
    asm volatile("{\n.reg .pred P;\nelect.sync _|P, 0xffffffff;\nselp.u32 %0, 1, 0, P;\n}" : "=r"(p));
    return p != 0;
}
__device__ __forceinline__ void mbar_init(uint32_t bar, uint32_t count) {
    asm volatile("mbarrier.init.shared::cta.b64 [%0], %1;" :: "r"(bar), "r"(count) : "memory");
}
__device__ __forceinline__ void mbar_expect_tx(uint32_t bar, uint32_t bytes) {
    asm volatile("mbarrier.arrive.expect_tx.shared::cta.b64 _, [%0], %1;" :: "r"(bar), "r"(bytes) : "memory");
}
__device__ __forceinline__ void mbar_arrive_cluster(uint32_t cluster_addr) {
    asm volatile("mbarrier.arrive.shared::cluster.b64 _, [%0];" :: "r"(cluster_addr) : "memory");
}
__device__ __forceinline__ uint32_t mapa(uint32_t addr, uint32_t cta) {
    uint32_t r;
    asm volatile("mapa.shared::cluster.u32 %0, %1, %2;" : "=r"(r) : "r"(addr), "r"(cta));
    return r;
}
__device__ __forceinline__ bool mbar_try_wait(uint32_t bar, uint32_t parity) {
    uint32_t ok;
    asm volatile("{\n.reg .pred p;\nmbarrier.try_wait.parity.shared::cta.b64 p, [%1], %2;\nselp.u32 %0, 1, 0, p;\n}"
                 : "=r"(ok) : "r"(bar), "r"(parity) : "memory");
    return ok != 0;
}
__device__ __forceinline__ void mbar_wait(uint32_t bar, uint32_t parity) {
    asm volatile("{\n.reg .pred p;\n.reg .u32 n;\n"
                 "mbarrier.try_wait.parity.shared::cta.b64 p, [%0], %1;\n@p bra DONE_%=;\nmov.u32 n, 0;\n"
                 "WAIT_%=:\nmbarrier.try_wait.parity.shared::cta.b64 p, [%0], %1;\n@p bra DONE_%=;\n"
                 "add.u32 n, n, 1;\nsetp.lt.u32 p, n, 4194304;\n@p bra WAIT_%=;\ntrap;\nDONE_%=:\n}"
                 :: "r"(bar), "r"(parity) : "memory");
}
__device__ __forceinline__ void tma2d_mc(uint32_t dst, const CUtensorMap* tm, uint32_t bar, int c0, int c1) {
    asm volatile("cp.async.bulk.tensor.2d.shared::cluster.global.mbarrier::complete_tx::bytes.multicast::cluster [%0], [%1, {%3, %4}], [%2], %5;"
                 :: "r"(dst), "l"(tm), "r"(bar), "r"(c0), "r"(c1), "h"((uint16_t)3) : "memory");
}
__device__ __forceinline__ void tma2d(uint32_t dst, const CUtensorMap* tm, uint32_t bar, int c0, int c1) {
    asm volatile("cp.async.bulk.tensor.2d.shared::cluster.global.mbarrier::complete_tx::bytes [%0], [%1, {%3, %4}], [%2];"
                 :: "r"(dst), "l"(tm), "r"(bar), "r"(c0), "r"(c1) : "memory");
}
__device__ __forceinline__ void ldsm4(uint32_t (&a)[4], uint32_t addr) {
    asm volatile("ldmatrix.sync.aligned.m8n8.x4.shared.b16 {%0,%1,%2,%3}, [%4];"
                 : "=r"(a[0]), "=r"(a[1]), "=r"(a[2]), "=r"(a[3]) : "r"(addr) : "memory");
}
__device__ __forceinline__ void cluster_arrive() { asm volatile("barrier.cluster.arrive.release.aligned;" ::: "memory"); }
__device__ __forceinline__ void cluster_wait() { asm volatile("barrier.cluster.wait.acquire.aligned;" ::: "memory"); }
__device__ __forceinline__ uint32_t cluster_rank() { uint32_t r; asm volatile("mov.u32 %0, %%cluster_ctarank;" : "=r"(r)); return r; }
__device__ __forceinline__ uint32_t sm_id() { uint32_t r; asm volatile("mov.u32 %0, %%smid;" : "=r"(r)); return r; }
__device__ __forceinline__ void named_bar_sync(int id, int n) { asm volatile("bar.sync %0, %1;" :: "r"(id), "r"(n) : "memory"); }
__device__ __forceinline__ void named_bar_arrive(int id, int n) { asm volatile("bar.arrive %0, %1;" :: "r"(id), "r"(n) : "memory"); }

__device__ __forceinline__ unsigned ld_acquire(const unsigned* p) {
    unsigned v; asm volatile("ld.acquire.gpu.global.u32 %0, [%1];" : "=r"(v) : "l"(p) : "memory"); return v;
}
__device__ __forceinline__ void red_release(unsigned* p, unsigned v) {
    asm volatile("red.release.gpu.global.add.u32 [%0], %1;" :: "l"(p), "r"(v) : "memory");
}
__device__ __forceinline__ void wait_flag(const unsigned* p, unsigned target) {
    asm volatile("{\n.reg .pred p;\n.reg .u32 n, v;\nmov.u32 n, 0;\n"
                 "WAIT_%=:\nld.acquire.gpu.global.u32 v, [%0];\nsetp.ge.u32 p, v, %1;\n@p bra DONE_%=;\n"
                 "add.u32 n, n, 1;\nsetp.lt.u32 p, n, 4194304;\n@p bra WAIT_%=;\ntrap;\nDONE_%=:\n}"
                 :: "l"(p), "r"(target) : "memory");
}
__device__ __forceinline__ uint4 ldg128(const void* p) {
    uint4 v;
    asm volatile("ld.global.L1::no_allocate.v4.u32 {%0,%1,%2,%3}, [%4];" : "=r"(v.x), "=r"(v.y), "=r"(v.z), "=r"(v.w) : "l"(p) : "memory");
    return v;
}
__device__ __forceinline__ float4 ldg128f(const void* p) {
    float4 v;
    asm volatile("ld.global.L1::no_allocate.v4.f32 {%0,%1,%2,%3}, [%4];" : "=f"(v.x), "=f"(v.y), "=f"(v.z), "=f"(v.w) : "l"(p) : "memory");
    return v;
}
__device__ __forceinline__ uint32_t ldg32(const void* p) {
    uint32_t v;
    asm volatile("ld.global.L1::no_allocate.u32 %0, [%1];" : "=r"(v) : "l"(p) : "memory");
    return v;
}
__device__ __forceinline__ void stg128(void* p, uint32_t a, uint32_t b, uint32_t c, uint32_t d) {
    asm volatile("st.global.v4.u32 [%0], {%1,%2,%3,%4};" :: "l"(p), "r"(a), "r"(b), "r"(c), "r"(d) : "memory");
}
__device__ __forceinline__ void sts128(uint32_t addr, uint32_t a, uint32_t b, uint32_t c, uint32_t d) {
    asm volatile("st.shared.v4.u32 [%0], {%1,%2,%3,%4};" :: "r"(addr), "r"(a), "r"(b), "r"(c), "r"(d) : "memory");
}
__device__ __forceinline__ uint4 lds128(uint32_t addr) {
    uint4 v;
    asm volatile("ld.shared.v4.u32 {%0,%1,%2,%3}, [%4];" : "=r"(v.x), "=r"(v.y), "=r"(v.z), "=r"(v.w) : "r"(addr) : "memory");
    return v;
}
__device__ __forceinline__ uint32_t pack2(float lo, float hi) {
    uint32_t r; asm("cvt.rn.bf16x2.f32 %0, %1, %2;" : "=r"(r) : "f"(hi), "f"(lo)); return r;
}
__device__ __forceinline__ float bf_lo(uint32_t u) { return __uint_as_float(u << 16); }
__device__ __forceinline__ float bf_hi(uint32_t u) { return __uint_as_float(u & 0xffff0000u); }
__device__ __forceinline__ uint32_t hsub2(uint32_t a, uint32_t b) {
    uint32_t r; asm("sub.rn.bf16x2 %0, %1, %2;" : "=r"(r) : "r"(a), "r"(b)); return r;
}
__device__ __forceinline__ uint32_t movmat(uint32_t a) {
    uint32_t d; asm volatile("movmatrix.sync.aligned.m8n8.trans.b16 %0, %1;" : "=r"(d) : "r"(a)); return d;
}
__device__ __forceinline__ void mma16816(float (&d)[4], uint32_t a0, uint32_t a1, uint32_t a2, uint32_t a3, uint32_t b0, uint32_t b1) {
    asm volatile("mma.sync.aligned.m16n8k16.row.col.f32.bf16.bf16.f32 {%0,%1,%2,%3}, {%4,%5,%6,%7}, {%8,%9}, {%0,%1,%2,%3};"
                 : "+f"(d[0]), "+f"(d[1]), "+f"(d[2]), "+f"(d[3]) : "r"(a0), "r"(a1), "r"(a2), "r"(a3), "r"(b0), "r"(b1));
}
__device__ __forceinline__ float ex2(float x) { float y; asm("ex2.approx.ftz.f32 %0, %1;" : "=f"(y) : "f"(x)); return y; }

__device__ __forceinline__ void wgmma_fence() { asm volatile("wgmma.fence.sync.aligned;" ::: "memory"); }
__device__ __forceinline__ void wgmma_commit() { asm volatile("wgmma.commit_group.sync.aligned;" ::: "memory"); }
template <int N> __device__ __forceinline__ void wgmma_wait() { asm volatile("wgmma.wait_group.sync.aligned %0;" :: "n"(N) : "memory"); }

__device__ __forceinline__ void wgmma_n64(float (&d)[32], const uint32_t (&a)[4], uint64_t descB, int scaleD) {
    asm volatile("{\n.reg .pred p;\nsetp.ne.b32 p, %37, 0;\n"
        "wgmma.mma_async.sync.aligned.m64n64k16.f32.bf16.bf16 "
        "{%0, %1, %2, %3, %4, %5, %6, %7, %8, %9, %10, %11, %12, %13, %14, %15, "
        "%16, %17, %18, %19, %20, %21, %22, %23, %24, %25, %26, %27, %28, %29, %30, %31}, "
        "{%32, %33, %34, %35}, %36, p, 1, 1, 1;\n}\n"
        : "+f"(d[0]), "+f"(d[1]), "+f"(d[2]), "+f"(d[3]), "+f"(d[4]), "+f"(d[5]), "+f"(d[6]), "+f"(d[7]),
          "+f"(d[8]), "+f"(d[9]), "+f"(d[10]), "+f"(d[11]), "+f"(d[12]), "+f"(d[13]), "+f"(d[14]), "+f"(d[15]),
          "+f"(d[16]), "+f"(d[17]), "+f"(d[18]), "+f"(d[19]), "+f"(d[20]), "+f"(d[21]), "+f"(d[22]), "+f"(d[23]),
          "+f"(d[24]), "+f"(d[25]), "+f"(d[26]), "+f"(d[27]), "+f"(d[28]), "+f"(d[29]), "+f"(d[30]), "+f"(d[31])
        : "r"(a[0]), "r"(a[1]), "r"(a[2]), "r"(a[3]), "l"(descB), "r"(scaleD));
}

struct Ring {
    uint32_t s, ph;
    uint32_t ring_base;
    uint32_t full0;
    uint32_t empty_remote;
    __device__ __forceinline__ void advance() { if (++s == NST) { s = 0; ph ^= 1; } }
    __device__ __forceinline__ void release(uint32_t stage, int lane) {
        if (lane < 2) mbar_arrive_cluster(empty_remote + stage * 8);
    }
};

template <bool SW64>
__device__ __forceinline__ uint64_t stage_desc(uint32_t addr) {
    uint32_t lo = ((addr & 0x3FFFFu) >> 4) | ((SW64 ? (8192u >> 4) : (8192u >> 4)) << 16);
    uint32_t hi = (SW64 ? (512u >> 4) : (1024u >> 4)) | ((SW64 ? 2u : 1u) << 30);
    return ((uint64_t)hi << 32) | lo;
}

template <bool SW64>
__device__ __forceinline__ void mma_chunk(float (&acc)[32], const uint32_t (&a)[32][4], Ring& r, int lane) {
    uint32_t prev = 0;
#pragma unroll
    for (int q = 0; q < 4; q++) {
        mbar_wait(r.full0 + r.s * 8, r.ph);
        uint64_t desc = stage_desc<SW64>(r.ring_base + r.s * STAGE_BYTES);
        wgmma_fence();
#pragma unroll
        for (int k = 0; k < 8; k++)
            wgmma_n64(acc, a[q * 8 + k], desc + (uint64_t)(k * (SW64 ? 64 : 128)), (q | k) != 0);
        wgmma_commit();
        if (q > 0) { wgmma_wait<1>(); r.release(prev, lane); }
        prev = r.s;
        r.advance();
    }
    wgmma_wait<0>();
    r.release(prev, lane);
}

__device__ __forceinline__ void load_frags(uint32_t (&a)[32][4], const uint4* src) {
#pragma unroll
    for (int k = 0; k < 32; k++) {
        uint4 v = ldg128(src + k * 128);
        a[k][0] = v.x; a[k][1] = v.y; a[k][2] = v.z; a[k][3] = v.w;
    }
}

__device__ __forceinline__ void center(uint32_t (&a)[32][4], float mean0, float mean1) {
    uint32_t m0 = pack2(mean0, mean0), m1 = pack2(mean1, mean1);
#pragma unroll
    for (int k = 0; k < 32; k++) {
        a[k][0] = hsub2(a[k][0], m0); a[k][1] = hsub2(a[k][1], m1);
        a[k][2] = hsub2(a[k][2], m0); a[k][3] = hsub2(a[k][3], m1);
    }
}

__device__ __forceinline__ void combine_stats(const float4* st, int lane, float& mean0, float& mean1, float& rstd0, float& rstd1) {
    const int g = lane >> 2, t4 = lane & 3;
    float4 p = ldg128f(st + (2 * t4) * 8 + g), q = ldg128f(st + (2 * t4 + 1) * 8 + g);
    float s0 = p.x + q.x, s1 = p.z + q.z;
    s0 += __shfl_xor_sync(~0u, s0, 1); s1 += __shfl_xor_sync(~0u, s1, 1);
    s0 += __shfl_xor_sync(~0u, s0, 2); s1 += __shfl_xor_sync(~0u, s1, 2);
    mean0 = s0 * 0.125f; mean1 = s1 * 0.125f;
    float d0 = p.x - mean0, e0 = q.x - mean0, d1 = p.z - mean1, e1 = q.z - mean1;
    float m0 = p.y + q.y + 64.f * (d0 * d0 + e0 * e0), m1 = p.w + q.w + 64.f * (d1 * d1 + e1 * e1);
    m0 += __shfl_xor_sync(~0u, m0, 1); m1 += __shfl_xor_sync(~0u, m1, 1);
    m0 += __shfl_xor_sync(~0u, m0, 2); m1 += __shfl_xor_sync(~0u, m1, 2);
    rstd0 = rsqrtf(m0 * (1.f / 512.f) + 1e-5f);
    rstd1 = rsqrtf(m1 * (1.f / 512.f) + 1e-5f);
}

__device__ __forceinline__ void residual_epilogue(const float (&acc)[32], const uint32_t (&res)[4][4], uint32_t (&xo)[4][4],
                                                  float4* st_out, int lane, bool want_stats) {
    float v[32];
#pragma unroll
    for (int q = 0; q < 4; q++) {
#pragma unroll
        for (int hh = 0; hh < 2; hh++) {
            const int c = (2 * q + hh) * 4;
            uint32_t r0 = res[q][hh * 2], r1 = res[q][hh * 2 + 1];
            uint32_t o0 = pack2(acc[c] + bf_lo(r0), acc[c + 1] + bf_hi(r0));
            uint32_t o1 = pack2(acc[c + 2] + bf_lo(r1), acc[c + 3] + bf_hi(r1));
            xo[q][hh * 2] = o0; xo[q][hh * 2 + 1] = o1;
            v[c] = bf_lo(o0); v[c + 1] = bf_hi(o0); v[c + 2] = bf_lo(o1); v[c + 3] = bf_hi(o1);
        }
    }
    if (want_stats) {
        float s0 = 0.f, s1 = 0.f;
#pragma unroll
        for (int c = 0; c < 8; c++) { s0 += v[4 * c] + v[4 * c + 1]; s1 += v[4 * c + 2] + v[4 * c + 3]; }
        s0 += __shfl_xor_sync(~0u, s0, 1); s1 += __shfl_xor_sync(~0u, s1, 1);
        s0 += __shfl_xor_sync(~0u, s0, 2); s1 += __shfl_xor_sync(~0u, s1, 2);
        const float m0 = s0 * (1.f / 64.f), m1 = s1 * (1.f / 64.f);
        float q0 = 0.f, q1 = 0.f;
#pragma unroll
        for (int c = 0; c < 8; c++) {
            float a = v[4 * c] - m0, b = v[4 * c + 1] - m0, d = v[4 * c + 2] - m1, e = v[4 * c + 3] - m1;
            q0 += a * a + b * b; q1 += d * d + e * e;
        }
        q0 += __shfl_xor_sync(~0u, q0, 1); q1 += __shfl_xor_sync(~0u, q1, 1);
        q0 += __shfl_xor_sync(~0u, q0, 2); q1 += __shfl_xor_sync(~0u, q1, 2);
        if ((lane & 3) == 0) {
            asm volatile("st.global.v4.f32 [%0], {%1,%2,%3,%4};" :: "l"(st_out + (lane >> 2)), "f"(m0), "f"(q0), "f"(m1), "f"(q1) : "memory");
        }
    }
}

__device__ __forceinline__ void signal_flag(unsigned* f, int lane) {
    __syncwarp();
    if (lane == 0) red_release(f, 1);
}

__global__ void __launch_bounds__(NTHREADS, 1) fused_kernel(const __grid_constant__ Params P) {
    extern __shared__ __align__(1024) uint8_t smem[];
    const uint32_t sbase = smem_u32(smem);
    const uint32_t bar_full = sbase + SM_BAR, bar_empty = bar_full + NST * 8, role_addr = bar_empty + NST * 8;
    const int tid = threadIdx.x, warp = tid >> 5, lane = tid & 31;
    const uint32_t rank = cluster_rank();

    if (tid == 0) {
        if (sbase & 1023u) __trap();
        for (int s = 0; s < NST; s++) { mbar_init(bar_full + s * 8, 1); mbar_init(bar_empty + s * 8, 16); }
        asm volatile("fence.mbarrier_init.release.cluster;" ::: "memory");
    }
    if (tid == 32 && rank == 0) {
        const int gam = P.gpc_of_tpc[sm_id() >> 1] & 7;
        unsigned long long old = atomicAdd(&g_ticket, 1ull << (8 * gam));
        int tk = (int)((old >> (8 * gam)) & 0xFF);
        int role = gam * 8 + tk;
        if (tk >= 8) {
            unsigned long long cur; uint32_t n = 0;
            for (;;) {
                asm volatile("ld.relaxed.gpu.global.u64 %0, [%1];" : "=l"(cur) : "l"(&g_ticket) : "memory");
                int tot = 0;
                for (int g = 0; g < 8; g++) tot += (int)((cur >> (8 * g)) & 0xFF);
                if (tot >= NCLUSTERS) break;
                if (++n > SPIN_LIMIT) __trap();
            }
            int orank = tk - 8;
            for (int g = 0; g < gam; g++) { int c = (int)((cur >> (8 * g)) & 0xFF); if (c > 8) orank += c - 8; }
            role = -1;
            for (int g = 0; g < 8 && role < 0; g++) {
                int c = (int)((cur >> (8 * g)) & 0xFF);
                int fr = c < 8 ? 8 - c : 0;
                if (orank < fr) role = g * 8 + c + orank; else orank -= fr;
            }
        }
        asm volatile("st.shared::cluster.u32 [%0], %1;" :: "r"(mapa(role_addr, 0)), "r"(role) : "memory");
        asm volatile("st.shared::cluster.u32 [%0], %1;" :: "r"(mapa(role_addr, 1)), "r"(role) : "memory");
    }
    if (tid == 64) {
        asm volatile("prefetch.tensormap [%0];" :: "l"(&P.tm_x) : "memory");
        asm volatile("prefetch.tensormap [%0];" :: "l"(&P.tm_qkv) : "memory");
        asm volatile("prefetch.tensormap [%0];" :: "l"(&P.tm_wo) : "memory");
        asm volatile("prefetch.tensormap [%0];" :: "l"(&P.tm_wg) : "memory");
        asm volatile("prefetch.tensormap [%0];" :: "l"(&P.tm_wu) : "memory");
        asm volatile("prefetch.tensormap [%0];" :: "l"(&P.tm_wd) : "memory");
    }
    __syncwarp();
    cluster_arrive();
    cluster_wait();
    int role;
    asm volatile("ld.shared.u32 %0, [%1];" : "=r"(role) : "r"(role_addr) : "memory");
    const int grp = (role >> 3) * 2 + (int)rank;
    const int j = role & 7;

    if (warp >= 8) {
        asm volatile("setmaxnreg.dec.sync.aligned.u32 40;");
        if (warp == 8) {
            if (elect_one()) {
                uint32_t s = 0, ph = 0;
                const uint32_t xring = opaque(sbase + SM_RING), ring = opaque(sbase + SM_RING + rank * 8192u), fb = opaque(bar_full), eb = opaque(bar_empty);
                const int jj = (int)opaque((uint32_t)j), rk = (int)opaque(rank);
#define STAGE_BEGIN() do { mbar_wait(eb + s * 8, ph ^ 1); mbar_expect_tx(fb + s * 8, STAGE_BYTES); } while (0)
#define STAGE_END() do { if (++s == NST) { s = 0; ph ^= 1; } } while (0)
#pragma unroll 1
                for (int u = 0; u < 8; u++) {
                    STAGE_BEGIN();
                    const int xrow = ((u >> 2) * 16 + grp) * 64, xcol = (u & 3) * 128;
                    tma2d(xring + s * STAGE_BYTES, &P.tm_x, fb + s * 8, xcol, xrow);
                    tma2d(xring + s * STAGE_BYTES + 8192, &P.tm_x, fb + s * 8, xcol + 64, xrow);
                    STAGE_END();
                }
#pragma unroll 1
                for (int l = 0; l < 2; l++) {
#pragma unroll 1
                    for (int c = 0; c < 3; c++) {
                        const int col = (c == 0 ? 512 : c == 1 ? 1024 : 0) + 64 * jj;
#pragma unroll 1
                        for (int q = 0; q < 4; q++) {
                            STAGE_BEGIN();
                            tma2d_mc(ring + s * STAGE_BYTES, &P.tm_qkv, fb + s * 8, col, q * 128 + rk * 64);
                            STAGE_END();
                        }
                    }
#pragma unroll 1
                    for (int q = 0; q < 4; q++) {
                        STAGE_BEGIN();
                        tma2d_mc(ring + s * STAGE_BYTES, &P.tm_wo, fb + s * 8, 64 * jj, q * 128 + rk * 64);
                        STAGE_END();
                    }
                    const CUtensorMap* tmu = rk == 0 ? &P.tm_wg : &P.tm_wu;
#pragma unroll 1
                    for (int c = 0; c < 7; c++) {
#pragma unroll 1
                        for (int q = 0; q < 4; q++) {
                            STAGE_BEGIN();
                            tma2d_mc(ring + s * STAGE_BYTES, tmu, fb + s * 8, 224 * jj + 32 * c, q * 128);
                            STAGE_END();
                        }
                    }
#pragma unroll 1
                    for (int q = 0; q < 14; q++) {
                        STAGE_BEGIN();
                        tma2d_mc(ring + s * STAGE_BYTES, &P.tm_wd, fb + s * 8, 64 * jj, q * 128 + rk * 64);
                        STAGE_END();
                    }
                }
            }
            __syncwarp();
        }
        cluster_arrive();
        cluster_wait();
        if (tid == 256 && rank == 0) {
            unsigned old = atomicAdd(&g_done, 1u);
            if (old == NCLUSTERS - 1) {

#pragma unroll 1
 for (int i = 0; i < N_FLAGS; i++) g_flag[i * FLAG_STRIDE] = 0;
                g_ticket = 0ull;
                g_done = 0;
            }
        }
    } else {
        asm volatile("setmaxnreg.inc.sync.aligned.u32 232;");
        const int wg = warp >> 2, w = warp & 3;
        const int t = wg * 16 + grp;
        const int g = lane >> 2, t4 = lane & 3;
        const int tw = w * 32 + lane;
        Ring r;
        r.s = 0; r.ph = 0;
        r.ring_base = sbase + SM_RING; r.full0 = bar_full;
        r.empty_remote = mapa(bar_empty, lane & 1);
        const uint32_t kv_base = sbase + SM_KV + wg * KV_BYTES;
        const int row0 = t * 64 + w * 16 + g;
        unsigned* flags = g_flag;

        uint32_t a[32][4];
        float acc[32];

        for (int l = 0; l < 2; l++) {
            float mean0, mean1, rstd0, rstd1;
            if (l == 0) {
                {
                    const int lr = w * 16 + (lane & 7) + ((lane >> 3) & 1) * 8;
                    const uint32_t rowoff = lr * 128, sw = lr & 7, hi = lane >> 4;
#pragma unroll
                    for (int u = 0; u < 8; u++) {
                        if ((u >> 2) == wg) {
                            mbar_wait(r.full0 + r.s * 8, r.ph);
                            const uint32_t sb = r.ring_base + r.s * STAGE_BYTES + rowoff;
#pragma unroll
                            for (int k = 0; k < 8; k++)
                                ldsm4(a[(u & 3) * 8 + k], sb + (k >> 2) * 8192 + ((((k & 3) * 2 + hi) ^ sw) << 4));
                            __syncwarp();
                        }
                        r.release(r.s, lane);
                        r.advance();
                    }
                }
                float sm[4][4];
#pragma unroll
                for (int c = 0; c < 4; c++) { sm[c][0] = sm[c][1] = sm[c][2] = sm[c][3] = 0.f; }
#pragma unroll
                for (int k = 0; k < 32; k++) mma16816(sm[k & 3], a[k][0], a[k][1], a[k][2], a[k][3], 0x3F803F80u, 0x3F803F80u);
                mean0 = (sm[0][0] + sm[1][0] + sm[2][0] + sm[3][0]) * (1.f / 512.f);
                mean1 = (sm[0][2] + sm[1][2] + sm[2][2] + sm[3][2]) * (1.f / 512.f);
                center(a, mean0, mean1);
                float d0[2][4], d1[2][4];
#pragma unroll
                for (int c = 0; c < 2; c++) { d0[c][0] = d0[c][1] = d0[c][2] = d0[c][3] = 0.f; d1[c][0] = d1[c][1] = d1[c][2] = d1[c][3] = 0.f; }
#pragma unroll
                for (int k = 0; k < 32; k++) {
                    mma16816(d0[k & 1], a[k][0], a[k][1], a[k][2], a[k][3], a[k][0], a[k][2]);
                    mma16816(d1[k & 1], a[k][0], a[k][1], a[k][2], a[k][3], a[k][1], a[k][3]);
                }
                float e0 = (g & 1) ? d0[0][1] + d0[1][1] : d0[0][0] + d0[1][0];
                float e1 = (g & 1) ? d1[0][3] + d1[1][3] : d1[0][2] + d1[1][2];
                const int src = g * 4 + (g >> 1);
                e0 = __shfl_sync(~0u, e0, src); e1 = __shfl_sync(~0u, e1, src);
                const float dl0 = mean0 - bf_lo(pack2(mean0, mean0)), dl1 = mean1 - bf_lo(pack2(mean1, mean1));
                rstd0 = rsqrtf(fmaxf(e0 * (1.f / 512.f) - dl0 * dl0, 0.f) + 1e-5f);
                rstd1 = rsqrtf(fmaxf(e1 * (1.f / 512.f) - dl1 * dl1, 0.f) + 1e-5f);
            } else {
                wait_flag(flags + (FL_X2 + t * 4 + w) * FLAG_STRIDE, 8);
                load_frags(a, g_x2 + (size_t)t * 32 * 128 + tw);
                combine_stats(g_st2 + (t * 4 + w) * 64, lane, mean0, mean1, rstd0, rstd1);
                center(a, mean0, mean1);
            }
            uint4* halo_out = g_halo + (size_t)((l * NT + t) * 8 + j) * 256 + lane;
            mma_chunk<false>(acc, a, r, lane);
#pragma unroll
            for (int h = 0; h < 4; h++) {
                uint32_t r0 = pack2(acc[8 * h] * rstd0, acc[8 * h + 1] * rstd0), r1 = pack2(acc[8 * h + 2] * rstd1, acc[8 * h + 3] * rstd1);
                uint32_t r2 = pack2(acc[8 * h + 4] * rstd0, acc[8 * h + 5] * rstd0), r3 = pack2(acc[8 * h + 6] * rstd1, acc[8 * h + 7] * rstd1);
                sts128(kv_base + (w * 8 + h) * 512 + lane * 16, r0, r1, r2, r3);
                if (w == 3) stg128(halo_out + h * 32, r0, r1, r2, r3);
            }
            mma_chunk<false>(acc, a, r, lane);
#pragma unroll
            for (int h = 0; h < 4; h++) {
                uint32_t r0 = pack2(acc[8 * h] * rstd0, acc[8 * h + 1] * rstd0), r1 = pack2(acc[8 * h + 2] * rstd1, acc[8 * h + 3] * rstd1);
                uint32_t r2 = pack2(acc[8 * h + 4] * rstd0, acc[8 * h + 5] * rstd0), r3 = pack2(acc[8 * h + 6] * rstd1, acc[8 * h + 7] * rstd1);
                r0 = movmat(r0); r1 = movmat(r1); r2 = movmat(r2); r3 = movmat(r3);
                sts128(kv_base + (w * 8 + 4 + h) * 512 + lane * 16, r0, r1, r2, r3);
                if (w == 3) stg128(halo_out + (4 + h) * 32, r0, r1, r2, r3);
            }
            if (w == 3) signal_flag(flags + (FL_HALO + t * 8 + j) * FLAG_STRIDE, lane);
            mma_chunk<false>(acc, a, r, lane);
            uint32_t qf[4][4];
#pragma unroll
            for (int h = 0; h < 4; h++) {
                qf[h][0] = pack2(acc[8 * h] * rstd0, acc[8 * h + 1] * rstd0); qf[h][1] = pack2(acc[8 * h + 2] * rstd1, acc[8 * h + 3] * rstd1);
                qf[h][2] = pack2(acc[8 * h + 4] * rstd0, acc[8 * h + 5] * rstd0); qf[h][3] = pack2(acc[8 * h + 6] * rstd1, acc[8 * h + 7] * rstd1);
            }
            named_bar_sync(1 + wg, 128);
            {
                const bool has_prev = (w > 0) || (t > 0);
                const uint4* halo_in = g_halo + (size_t)((l * NT + (t > 0 ? t - 1 : 0)) * 8 + j) * 256 + lane;
                if (w == 0 && t > 0) wait_flag(flags + (FL_HALO + (t - 1) * 8 + j) * FLAG_STRIDE, l + 1);
                const bool hi_t = t4 > (g >> 1);
                const bool odd = g & 1;
                constexpr float SC = 0.25f * 1.4426950408889634f;
                const float NEG = __int_as_float(0xff800000);
#pragma unroll
                for (int h = 0; h < 4; h++) {
                    uint4 kp, vp;
                    if (w > 0) {
                        kp = lds128(kv_base + ((w - 1) * 8 + h) * 512 + lane * 16);
                        vp = lds128(kv_base + ((w - 1) * 8 + 4 + h) * 512 + lane * 16);
                    } else if (t > 0) {
                        kp = ldg128(halo_in + h * 32); vp = ldg128(halo_in + (4 + h) * 32);
                    } else {
                        kp = make_uint4(0, 0, 0, 0); vp = kp;
                    }
                    uint4 ko = lds128(kv_base + (w * 8 + h) * 512 + lane * 16);
                    uint4 vo = lds128(kv_base + (w * 8 + 4 + h) * 512 + lane * 16);
                    float s0[4] = {0, 0, 0, 0}, s1[4] = {0, 0, 0, 0}, s2[4] = {0, 0, 0, 0}, s3[4] = {0, 0, 0, 0};
                    mma16816(s0, qf[h][0], qf[h][1], qf[h][2], qf[h][3], kp.x, kp.z);
                    mma16816(s1, qf[h][0], qf[h][1], qf[h][2], qf[h][3], kp.y, kp.w);
                    mma16816(s2, qf[h][0], qf[h][1], qf[h][2], qf[h][3], ko.x, ko.z);
                    mma16816(s3, qf[h][0], qf[h][1], qf[h][2], qf[h][3], ko.y, ko.w);
                    float t0g = odd ? s0[1] : s0[0], t1g = odd ? s1[1] : s1[0], t2g = odd ? s2[1] : s2[0];
                    float t1h = odd ? s1[3] : s1[2], t2h = odd ? s2[3] : s2[2], t3h = odd ? s3[3] : s3[2];
                    if (!has_prev) { t0g = NEG; t1g = NEG; t1h = NEG; }
                    float eg = hi_t ? t0g : t2g;
                    float eh = hi_t ? t1h : t3h;
                    float mg = fmaxf(eg, t1g), mh = fmaxf(eh, t2h);
                    mg = fmaxf(mg, __shfl_xor_sync(~0u, mg, 1)); mh = fmaxf(mh, __shfl_xor_sync(~0u, mh, 1));
                    mg = fmaxf(mg, __shfl_xor_sync(~0u, mg, 2)); mh = fmaxf(mh, __shfl_xor_sync(~0u, mh, 2));
                    float peg = ex2((eg - mg) * SC), p1g = ex2((t1g - mg) * SC);
                    float peh = ex2((eh - mh) * SC), p2h = ex2((t2h - mh) * SC);
                    float sg = peg + p1g, sh = peh + p2h;
                    sg += __shfl_xor_sync(~0u, sg, 1); sh += __shfl_xor_sync(~0u, sh, 1);
                    sg += __shfl_xor_sync(~0u, sg, 2); sh += __shfl_xor_sync(~0u, sh, 2);
                    const float ig = 1.f / sg, ih = 1.f / sh;
                    peg *= ig; p1g *= ig; peh *= ih; p2h *= ih;
                    const uint32_t sh16 = odd ? 16 : 0;
                    uint32_t beg = (pack2(peg, 0.f) & 0xffffu) << sh16, b1g = (pack2(p1g, 0.f) & 0xffffu) << sh16;
                    uint32_t beh = (pack2(peh, 0.f) & 0xffffu) << sh16, b2h = (pack2(p2h, 0.f) & 0xffffu) << sh16;
                    uint32_t pa0 = hi_t ? beg : 0u, pa3 = hi_t ? beh : 0u;
                    uint32_t pb0 = hi_t ? 0u : beg, pb3 = hi_t ? 0u : beh;
                    float o0[4] = {0, 0, 0, 0}, o1[4] = {0, 0, 0, 0};
                    mma16816(o0, pa0, 0u, b1g, pa3, vp.x, vp.y);
                    mma16816(o1, pa0, 0u, b1g, pa3, vp.z, vp.w);
                    mma16816(o0, pb0, b2h, 0u, pb3, vo.x, vo.y);
                    mma16816(o1, pb0, b2h, 0u, pb3, vo.z, vo.w);
                    stg128(g_o + ((size_t)t * 32 + 4 * j + h) * 128 + tw,
                           pack2(o0[0], o0[1]), pack2(o0[2], o0[3]), pack2(o1[0], o1[1]), pack2(o1[2], o1[3]));
                }
                signal_flag(flags + (FL_O + t * 4 + w) * FLAG_STRIDE, lane);
            }
            uint32_t res[4][4], xo[4][4];
            if (l == 0) {
                const __nv_bfloat16* xr = P.x + (size_t)row0 * DM + 64 * j + 2 * t4;
#pragma unroll
                for (int q = 0; q < 4; q++) {
                    res[q][0] = ldg32(xr + q * 16); res[q][1] = ldg32(xr + 8 * DM + q * 16);
                    res[q][2] = ldg32(xr + q * 16 + 8); res[q][3] = ldg32(xr + 8 * DM + q * 16 + 8);
                }
            } else {
#pragma unroll
                for (int q = 0; q < 4; q++) {
                    uint4 v = ldg128(g_x2 + ((size_t)t * 32 + 4 * j + q) * 128 + tw);
                    res[q][0] = v.x; res[q][1] = v.y; res[q][2] = v.z; res[q][3] = v.w;
                }
            }
            wait_flag(flags + (FL_O + t * 4 + w) * FLAG_STRIDE, 8 * (l + 1));
            load_frags(a, g_o + (size_t)t * 32 * 128 + tw);
            mma_chunk<false>(acc, a, r, lane);
            residual_epilogue(acc, res, xo, g_st1 + ((t * 4 + w) * 8 + j) * 8, lane, true);
#pragma unroll
            for (int q = 0; q < 4; q++)
                stg128(g_x1 + ((size_t)t * 32 + 4 * j + q) * 128 + tw, xo[q][0], xo[q][1], xo[q][2], xo[q][3]);
            signal_flag(flags + (FL_X1 + t * 4 + w) * FLAG_STRIDE, lane);
            wait_flag(flags + (FL_X1 + t * 4 + w) * FLAG_STRIDE, 8 * (l + 1));
            load_frags(a, g_x1 + (size_t)t * 32 * 128 + tw);
            combine_stats(g_st1 + (t * 4 + w) * 64, lane, mean0, mean1, rstd0, rstd1);
            center(a, mean0, mean1);
            {
                const float q0 = rstd0 * rstd0, q1 = rstd1 * rstd1;
                uint4* hdst = g_h + ((size_t)t * 112 + 14 * j) * 128 + tw;
#pragma unroll 1
                for (int c = 0; c < 7; c++) {
                    mma_chunk<true>(acc, a, r, lane);
#pragma unroll
                    for (int ks = 0; ks < 2; ks++) {
                        const int b = ks * 8;
                        stg128(hdst + (2 * c + ks) * 128,
                               pack2(acc[b] * acc[16 + b] * q0, acc[b + 1] * acc[17 + b] * q0),
                               pack2(acc[b + 2] * acc[18 + b] * q1, acc[b + 3] * acc[19 + b] * q1),
                               pack2(acc[b + 4] * acc[20 + b] * q0, acc[b + 5] * acc[21 + b] * q0),
                               pack2(acc[b + 6] * acc[22 + b] * q1, acc[b + 7] * acc[23 + b] * q1));
                    }
                }
                signal_flag(flags + (FL_H + t * 4 + w) * FLAG_STRIDE, lane);
            }
            wait_flag(flags + (FL_H + t * 4 + w) * FLAG_STRIDE, 8 * (l + 1));
            {
                const uint4* hsrc = g_h + (size_t)t * 112 * 128 + tw;
#pragma unroll
                for (int b = 0; b < 3; b++) {
#pragma unroll
                    for (int k = 0; k < 8; k++) {
                        uint4 v = ldg128(hsrc + (b * 8 + k) * 128);
                        a[b * 8 + k][0] = v.x; a[b * 8 + k][1] = v.y; a[b * 8 + k][2] = v.z; a[b * 8 + k][3] = v.w;
                    }
                }
                uint32_t prev = 0;
#pragma unroll
                for (int q = 0; q < 14; q++) {
                    mbar_wait(r.full0 + r.s * 8, r.ph);
                    uint64_t desc = stage_desc<false>(r.ring_base + r.s * STAGE_BYTES);
                    wgmma_fence();
#pragma unroll
                    for (int k = 0; k < 8; k++)
                        wgmma_n64(acc, a[(q & 3) * 8 + k], desc + (uint64_t)(k * 128), (q | k) != 0);
                    wgmma_commit();
                    if (q > 0) { wgmma_wait<1>(); r.release(prev, lane); }
                    prev = r.s;
                    r.advance();
                    if (q + 3 < 14) {
#pragma unroll
                        for (int k = 0; k < 8; k++) {
                            uint4 v = ldg128(hsrc + ((q + 3) * 8 + k) * 128);
                            const int b = ((q + 3) & 3) * 8 + k;
                            a[b][0] = v.x; a[b][1] = v.y; a[b][2] = v.z; a[b][3] = v.w;
                        }
                    }
                    if (q == 12) {
#pragma unroll
                        for (int qq = 0; qq < 4; qq++) {
                            uint4 v = ldg128(g_x1 + ((size_t)t * 32 + 4 * j + qq) * 128 + tw);
                            res[qq][0] = v.x; res[qq][1] = v.y; res[qq][2] = v.z; res[qq][3] = v.w;
                        }
                    }
                }
                wgmma_wait<0>();
                r.release(prev, lane);
            }
            residual_epilogue(acc, res, xo, g_st2 + ((t * 4 + w) * 8 + j) * 8, lane, l == 0);
            if (l == 0) {
#pragma unroll
                for (int q = 0; q < 4; q++)
                    stg128(g_x2 + ((size_t)t * 32 + 4 * j + q) * 128 + tw, xo[q][0], xo[q][1], xo[q][2], xo[q][3]);
                signal_flag(flags + (FL_X2 + t * 4 + w) * FLAG_STRIDE, lane);
            } else {
                __nv_bfloat16* o = P.out + (size_t)row0 * DM + 64 * j + 2 * t4;
#pragma unroll
                for (int q = 0; q < 4; q++) {
                    *(uint32_t*)(o + q * 16) = xo[q][0]; *(uint32_t*)(o + 8 * DM + q * 16) = xo[q][1];
                    *(uint32_t*)(o + q * 16 + 8) = xo[q][2]; *(uint32_t*)(o + 8 * DM + q * 16 + 8) = xo[q][3];
                }
            }
        }
        cluster_arrive();
        cluster_wait();
    }
}

typedef CUresult (*EncodeFn)(CUtensorMap*, CUtensorMapDataType, cuuint32_t, void*, const cuuint64_t*, const cuuint64_t*,
                             const cuuint32_t*, const cuuint32_t*, CUtensorMapInterleave, CUtensorMapSwizzle,
                             CUtensorMapL2promotion, CUtensorMapFloatOOBfill);

void encode_2d(EncodeFn enc, CUtensorMap* tm, const void* ptr, uint64_t cols, uint64_t rows, uint32_t box_c, uint32_t box_r, CUtensorMapSwizzle sw) {
    cuuint64_t dims[2] = {cols, rows};
    cuuint64_t strides[1] = {cols * 2};
    cuuint32_t box[2] = {box_c, box_r};
    cuuint32_t es[2] = {1, 1};
    enc(tm, CU_TENSOR_MAP_DATA_TYPE_BFLOAT16, 2, const_cast<void*>(ptr), dims, strides, box, es, CU_TENSOR_MAP_INTERLEAVE_NONE, sw,
        CU_TENSOR_MAP_L2_PROMOTION_L2_128B, CU_TENSOR_MAP_FLOAT_OOB_FILL_NONE);
}

void build_gpc_table(unsigned char* table) {
    int M[10] = {0};
    bool ok = true;
    for (int c = 1; c <= 8 && ok; c++) {
        cudaLaunchConfig_t cfg = {};
        cfg.gridDim = dim3(2 * c); cfg.blockDim = dim3(NTHREADS); cfg.dynamicSmemBytes = SM_TOTAL;
        cudaLaunchAttribute at[1];
        at[0].id = cudaLaunchAttributeClusterDimension; at[0].val.clusterDim.x = 2 * c; at[0].val.clusterDim.y = 1; at[0].val.clusterDim.z = 1;
        cfg.attrs = at; cfg.numAttrs = 1;
        if (cudaOccupancyMaxActiveClusters(&M[c], fused_kernel, &cfg) != cudaSuccess) { ok = false; (void)cudaGetLastError(); }
    }
    int n[10] = {0};
    bool found = false;
    if (ok) {
        for (int n9 = 0; n9 <= 8 && !found; n9++) for (int n8 = 0; n8 + n9 <= 8 && !found; n8++)
        for (int n7 = 0; n7 + n8 + n9 <= 8 && !found; n7++) for (int n6 = 0; n6 + n7 + n8 + n9 <= 8 && !found; n6++)
        for (int n5 = 0; n5 + n6 + n7 + n8 + n9 <= 8 && !found; n5++) for (int n4 = 0; n4 + n5 + n6 + n7 + n8 + n9 <= 8 && !found; n4++)
        for (int n3 = 0; n3 + n4 + n5 + n6 + n7 + n8 + n9 <= 8 && !found; n3++)
        for (int n2 = 0; n2 + n3 + n4 + n5 + n6 + n7 + n8 + n9 <= 8 && !found; n2++) {
            int cnt[10] = {0, 0, n2, n3, n4, n5, n6, n7, n8, n9};
            int tot = 0; for (int T = 2; T <= 9; T++) tot += T * cnt[T];
            cnt[1] = M[1] - tot;
            if (cnt[1] < 0) continue;
            bool match = true;
            for (int c = 2; c <= 8 && match; c++) { int m = 0; for (int T = 1; T <= 9; T++) m += cnt[T] * (T / c); match = (m == M[c]); }
            if (match) { for (int T = 1; T <= 9; T++) n[T] = cnt[T]; found = true; }
        }
    }
    for (int i = 0; i < 80; i++) table[i] = (unsigned char)(i & 7);
    if (!found) return;
    int size[8], ng = 0;
    for (int T = 2; T <= 9; T++) for (int k = 0; k < n[T] && ng < 8; k++) size[ng++] = T;
    int id = 0, fill[8] = {0};
    for (int rnd = 0; rnd < 9; rnd++) for (int gI = 0; gI < ng; gI++) if (size[gI] > rnd && id < 80) { table[id++] = (unsigned char)gI; fill[gI]++; }
    for (int k = 0; k < n[1] && id < 80; k++) {
        int best = 0; for (int gI = 1; gI < 8; gI++) if (fill[gI] < fill[best]) best = gI;
        table[id++] = (unsigned char)best; fill[best]++;
    }
}

}

extern "C" void kernel_launch(void* const* d_in, const int* in_sizes, int n_in, void* d_out, int out_size) {
    (void)in_sizes; (void)n_in; (void)out_size;
    static Params P;
    static bool init = false;
    static const void* cached[8] = {nullptr};
    bool same = init;
    for (int i = 0; i < 7 && same; i++) same = (cached[i] == d_in[i]);
    same = same && cached[7] == d_out;
    if (!same) {
        void* fn = nullptr;
        cudaDriverEntryPointQueryResult st;
        cudaGetDriverEntryPoint("cuTensorMapEncodeTiled", &fn, cudaEnableDefault, &st);
        EncodeFn enc = (EncodeFn)fn;
        const void* wqkv = d_in[1]; const void* wo = d_in[2];
        const void* wg = d_in[4]; const void* wu = d_in[5]; const void* wd = d_in[6];
        encode_2d(enc, &P.tm_x, d_in[0], 512, 2048, 64, 64, CU_TENSOR_MAP_SWIZZLE_128B);
        encode_2d(enc, &P.tm_qkv, wqkv, 1536, 512, 64, 64, CU_TENSOR_MAP_SWIZZLE_128B);
        encode_2d(enc, &P.tm_wo, wo, 512, 512, 64, 64, CU_TENSOR_MAP_SWIZZLE_128B);
        encode_2d(enc, &P.tm_wg, wg, 1792, 512, 32, 128, CU_TENSOR_MAP_SWIZZLE_64B);
        encode_2d(enc, &P.tm_wu, wu, 1792, 512, 32, 128, CU_TENSOR_MAP_SWIZZLE_64B);
        encode_2d(enc, &P.tm_wd, wd, 512, 1792, 64, 64, CU_TENSOR_MAP_SWIZZLE_128B);
        P.x = (const __nv_bfloat16*)d_in[0];
        P.out = (__nv_bfloat16*)d_out;
        if (!init) {
            cudaFuncSetAttribute(fused_kernel, cudaFuncAttributeMaxDynamicSharedMemorySize, SM_TOTAL);
            cudaFuncSetAttribute(fused_kernel, cudaFuncAttributeNonPortableClusterSizeAllowed, 1);
            build_gpc_table(P.gpc_of_tpc);
        }
        for (int i = 0; i < 7; i++) cached[i] = d_in[i];
        cached[7] = d_out;
        init = true;
    }
    cudaLaunchConfig_t cfg = {};
    cfg.gridDim = dim3(2 * NCLUSTERS); cfg.blockDim = dim3(NTHREADS); cfg.dynamicSmemBytes = SM_TOTAL;
    cfg.stream = cudaStreamPerThread;
    cudaLaunchAttribute at[1];
    at[0].id = cudaLaunchAttributeClusterDimension; at[0].val.clusterDim.x = 2; at[0].val.clusterDim.y = 1; at[0].val.clusterDim.z = 1;
    cfg.attrs = at; cfg.numAttrs = 1;
    cudaLaunchKernelEx(&cfg, fused_kernel, P);
}
```

```cpp
#include <cuda_runtime.h>
#include <cuda_bf16.h>
#include <cuda.h>
#include <stdint.h>

namespace {

constexpr int S_LEN = 2048, DM = 512, FF = 1792;
constexpr int NT = 32;
constexpr int NST = 12;
constexpr int STAGE_BYTES = 16384;
constexpr int KV_BYTES = 16384;
constexpr int SM_RING = 0;
constexpr int SM_KV = NST * STAGE_BYTES;
constexpr int SM_BAR = SM_KV + 2 * KV_BYTES;
constexpr int SM_TOTAL = SM_BAR + 256;
constexpr int NTHREADS = 384;
constexpr int NCLUSTERS = 64;
constexpr int STAGES_PER_LAYER = 12 + 4 + 28 + 14;
constexpr unsigned SPIN_LIMIT = 1u << 22;

__device__ uint4 g_o[NT * 32 * 128];
__device__ uint4 g_x1[NT * 32 * 128];
__device__ uint4 g_x2[NT * 32 * 128];
__device__ uint4 g_h[NT * 112 * 128];
__device__ float4 g_st1[NT * 4 * 8 * 8];
__device__ float4 g_st2[NT * 4 * 8 * 8];
__device__ uint4 g_halo[2 * NT * 8 * 2 * 4 * 32];
constexpr int FLAG_STRIDE = 16;
constexpr int FL_O = 0, FL_X1 = 128, FL_H = 256, FL_X2 = 384, FL_HALO = 512;
constexpr int N_FLAGS = 768;
__device__ unsigned g_flag[N_FLAGS * FLAG_STRIDE];
__device__ unsigned long long g_ticket;
__device__ unsigned g_done;

#define TICK(idx) do {} while (0)

struct Params {
    CUtensorMap tm_x;
    CUtensorMap tm_qkv;
    CUtensorMap tm_wo;
    CUtensorMap tm_wg;
    CUtensorMap tm_wu;
    CUtensorMap tm_wd;
    const __nv_bfloat16* x;
    __nv_bfloat16* out;
    unsigned char gpc_of_tpc[80];
};

__device__ __forceinline__ uint32_t smem_u32(const void* p) { return (uint32_t)__cvta_generic_to_shared(p); }
__device__ __forceinline__ uint32_t opaque(uint32_t x) { uint32_t y; asm volatile("mov.u32 %0, %1;" : "=r"(y) : "r"(x)); return y; }
__device__ __forceinline__ bool elect_one() {
    uint32_t p;
    asm volatile("{\n.reg .pred P;\nelect.sync _|P, 0xffffffff;\nselp.u32 %0, 1, 0, P;\n}" : "=r"(p));
    return p != 0;
}
__device__ __forceinline__ void mbar_init(uint32_t bar, uint32_t count) {
    asm volatile("mbarrier.init.shared::cta.b64 [%0], %1;" :: "r"(bar), "r"(count) : "memory");
}
__device__ __forceinline__ void mbar_expect_tx(uint32_t bar, uint32_t bytes) {
    asm volatile("mbarrier.arrive.expect_tx.shared::cta.b64 _, [%0], %1;" :: "r"(bar), "r"(bytes) : "memory");
}
__device__ __forceinline__ void mbar_arrive_cluster(uint32_t cluster_addr) {
    asm volatile("mbarrier.arrive.shared::cluster.b64 _, [%0];" :: "r"(cluster_addr) : "memory");
}
__device__ __forceinline__ uint32_t mapa(uint32_t addr, uint32_t cta) {
    uint32_t r;
    asm volatile("mapa.shared::cluster.u32 %0, %1, %2;" : "=r"(r) : "r"(addr), "r"(cta));
    return r;
}
__device__ __forceinline__ bool mbar_try_wait(uint32_t bar, uint32_t parity) {
    uint32_t ok;
    asm volatile("{\n.reg .pred p;\nmbarrier.try_wait.parity.shared::cta.b64 p, [%1], %2;\nselp.u32 %0, 1, 0, p;\n}"
                 : "=r"(ok) : "r"(bar), "r"(parity) : "memory");
    return ok != 0;
}
__device__ __forceinline__ void mbar_wait(uint32_t bar, uint32_t parity) {
    asm volatile("{\n.reg .pred p;\n.reg .u32 n;\n"
                 "mbarrier.try_wait.parity.shared::cta.b64 p, [%0], %1;\n@p bra DONE_%=;\nmov.u32 n, 0;\n"
                 "WAIT_%=:\nmbarrier.try_wait.parity.shared::cta.b64 p, [%0], %1;\n@p bra DONE_%=;\n"
                 "add.u32 n, n, 1;\nsetp.lt.u32 p, n, 4194304;\n@p bra WAIT_%=;\ntrap;\nDONE_%=:\n}"
                 :: "r"(bar), "r"(parity) : "memory");
}
__device__ __forceinline__ void tma2d_mc(uint32_t dst, const CUtensorMap* tm, uint32_t bar, int c0, int c1) {
    asm volatile("cp.async.bulk.tensor.2d.shared::cluster.global.mbarrier::complete_tx::bytes.multicast::cluster [%0], [%1, {%3, %4}], [%2], %5;"
                 :: "r"(dst), "l"(tm), "r"(bar), "r"(c0), "r"(c1), "h"((uint16_t)3) : "memory");
}
__device__ __forceinline__ void tma2d(uint32_t dst, const CUtensorMap* tm, uint32_t bar, int c0, int c1) {
    asm volatile("cp.async.bulk.tensor.2d.shared::cluster.global.mbarrier::complete_tx::bytes [%0], [%1, {%3, %4}], [%2];"
                 :: "r"(dst), "l"(tm), "r"(bar), "r"(c0), "r"(c1) : "memory");
}
__device__ __forceinline__ void ldsm4(uint32_t (&a)[4], uint32_t addr) {
    asm volatile("ldmatrix.sync.aligned.m8n8.x4.shared.b16 {%0,%1,%2,%3}, [%4];"
                 : "=r"(a[0]), "=r"(a[1]), "=r"(a[2]), "=r"(a[3]) : "r"(addr) : "memory");
}
__device__ __forceinline__ void cluster_arrive() { asm volatile("barrier.cluster.arrive.release.aligned;" ::: "memory"); }
__device__ __forceinline__ void cluster_wait() { asm volatile("barrier.cluster.wait.acquire.aligned;" ::: "memory"); }
__device__ __forceinline__ uint32_t cluster_rank() { uint32_t r; asm volatile("mov.u32 %0, %%cluster_ctarank;" : "=r"(r)); return r; }
__device__ __forceinline__ uint32_t sm_id() { uint32_t r; asm volatile("mov.u32 %0, %%smid;" : "=r"(r)); return r; }
__device__ __forceinline__ void named_bar_sync(int id, int n) { asm volatile("bar.sync %0, %1;" :: "r"(id), "r"(n) : "memory"); }
__device__ __forceinline__ void named_bar_arrive(int id, int n) { asm volatile("bar.arrive %0, %1;" :: "r"(id), "r"(n) : "memory"); }

__device__ __forceinline__ unsigned ld_acquire(const unsigned* p) {
    unsigned v; asm volatile("ld.acquire.gpu.global.u32 %0, [%1];" : "=r"(v) : "l"(p) : "memory"); return v;
}
__device__ __forceinline__ void red_release(unsigned* p, unsigned v) {
    asm volatile("red.release.gpu.global.add.u32 [%0], %1;" :: "l"(p), "r"(v) : "memory");
}
__device__ __forceinline__ void wait_flag(const unsigned* p, unsigned target) {
    asm volatile("{\n.reg .pred p;\n.reg .u32 n, v;\nmov.u32 n, 0;\n"
                 "WAIT_%=:\nld.acquire.gpu.global.u32 v, [%0];\nsetp.ge.u32 p, v, %1;\n@p bra DONE_%=;\n"
                 "add.u32 n, n, 1;\nsetp.lt.u32 p, n, 4194304;\n@p bra WAIT_%=;\ntrap;\nDONE_%=:\n}"
                 :: "l"(p), "r"(target) : "memory");
}
__device__ __forceinline__ uint4 ldg128(const void* p) {
    uint4 v;
    asm volatile("ld.global.L1::no_allocate.v4.u32 {%0,%1,%2,%3}, [%4];" : "=r"(v.x), "=r"(v.y), "=r"(v.z), "=r"(v.w) : "l"(p) : "memory");
    return v;
}
__device__ __forceinline__ float4 ldg128f(const void* p) {
    float4 v;
    asm volatile("ld.global.L1::no_allocate.v4.f32 {%0,%1,%2,%3}, [%4];" : "=f"(v.x), "=f"(v.y), "=f"(v.z), "=f"(v.w) : "l"(p) : "memory");
    return v;
}
__device__ __forceinline__ uint32_t ldg32(const void* p) {
    uint32_t v;
    asm volatile("ld.global.L1::no_allocate.u32 %0, [%1];" : "=r"(v) : "l"(p) : "memory");
    return v;
}
__device__ __forceinline__ void stg128(void* p, uint32_t a, uint32_t b, uint32_t c, uint32_t d) {
    asm volatile("st.global.v4.u32 [%0], {%1,%2,%3,%4};" :: "l"(p), "r"(a), "r"(b), "r"(c), "r"(d) : "memory");
}
__device__ __forceinline__ void sts128(uint32_t addr, uint32_t a, uint32_t b, uint32_t c, uint32_t d) {
    asm volatile("st.shared.v4.u32 [%0], {%1,%2,%3,%4};" :: "r"(addr), "r"(a), "r"(b), "r"(c), "r"(d) : "memory");
}
__device__ __forceinline__ uint4 lds128(uint32_t addr) {
    uint4 v;
    asm volatile("ld.shared.v4.u32 {%0,%1,%2,%3}, [%4];" : "=r"(v.x), "=r"(v.y), "=r"(v.z), "=r"(v.w) : "r"(addr) : "memory");
    return v;
}
__device__ __forceinline__ uint32_t pack2(float lo, float hi) {
    uint32_t r; asm("cvt.rn.bf16x2.f32 %0, %1, %2;" : "=r"(r) : "f"(hi), "f"(lo)); return r;
}
__device__ __forceinline__ float bf_lo(uint32_t u) { return __uint_as_float(u << 16); }
__device__ __forceinline__ float bf_hi(uint32_t u) { return __uint_as_float(u & 0xffff0000u); }
__device__ __forceinline__ uint32_t hsub2(uint32_t a, uint32_t b) {
    uint32_t r; asm("sub.rn.bf16x2 %0, %1, %2;" : "=r"(r) : "r"(a), "r"(b)); return r;
}
__device__ __forceinline__ uint32_t movmat(uint32_t a) {
    uint32_t d; asm volatile("movmatrix.sync.aligned.m8n8.trans.b16 %0, %1;" : "=r"(d) : "r"(a)); return d;
}
__device__ __forceinline__ void mma16816(float (&d)[4], uint32_t a0, uint32_t a1, uint32_t a2, uint32_t a3, uint32_t b0, uint32_t b1) {
    asm volatile("mma.sync.aligned.m16n8k16.row.col.f32.bf16.bf16.f32 {%0,%1,%2,%3}, {%4,%5,%6,%7}, {%8,%9}, {%0,%1,%2,%3};"
                 : "+f"(d[0]), "+f"(d[1]), "+f"(d[2]), "+f"(d[3]) : "r"(a0), "r"(a1), "r"(a2), "r"(a3), "r"(b0), "r"(b1));
}
__device__ __forceinline__ float ex2(float x) { float y; asm("ex2.approx.ftz.f32 %0, %1;" : "=f"(y) : "f"(x)); return y; }

__device__ __forceinline__ void wgmma_fence() { asm volatile("wgmma.fence.sync.aligned;" ::: "memory"); }
__device__ __forceinline__ void wgmma_commit() { asm volatile("wgmma.commit_group.sync.aligned;" ::: "memory"); }
template <int N> __device__ __forceinline__ void wgmma_wait() { asm volatile("wgmma.wait_group.sync.aligned %0;" :: "n"(N) : "memory"); }

__device__ __forceinline__ void wgmma_n64(float (&d)[32], const uint32_t (&a)[4], uint64_t descB, int scaleD) {
    asm volatile("{\n.reg .pred p;\nsetp.ne.b32 p, %37, 0;\n"
        "wgmma.mma_async.sync.aligned.m64n64k16.f32.bf16.bf16 "
        "{%0, %1, %2, %3, %4, %5, %6, %7, %8, %9, %10, %11, %12, %13, %14, %15, "
        "%16, %17, %18, %19, %20, %21, %22, %23, %24, %25, %26, %27, %28, %29, %30, %31}, "
        "{%32, %33, %34, %35}, %36, p, 1, 1, 1;\n}\n"
        : "+f"(d[0]), "+f"(d[1]), "+f"(d[2]), "+f"(d[3]), "+f"(d[4]), "+f"(d[5]), "+f"(d[6]), "+f"(d[7]),
          "+f"(d[8]), "+f"(d[9]), "+f"(d[10]), "+f"(d[11]), "+f"(d[12]), "+f"(d[13]), "+f"(d[14]), "+f"(d[15]),
          "+f"(d[16]), "+f"(d[17]), "+f"(d[18]), "+f"(d[19]), "+f"(d[20]), "+f"(d[21]), "+f"(d[22]), "+f"(d[23]),
          "+f"(d[24]), "+f"(d[25]), "+f"(d[26]), "+f"(d[27]), "+f"(d[28]), "+f"(d[29]), "+f"(d[30]), "+f"(d[31])
        : "r"(a[0]), "r"(a[1]), "r"(a[2]), "r"(a[3]), "l"(descB), "r"(scaleD));
}

struct Ring {
    uint32_t s, ph;
    uint32_t ring_base;
    uint32_t full0;
    uint32_t empty_remote;
    __device__ __forceinline__ void advance() { if (++s == NST) { s = 0; ph ^= 1; } }
    __device__ __forceinline__ void release(uint32_t stage, int lane) {
        if (lane < 2) mbar_arrive_cluster(empty_remote + stage * 8);
    }
};

template <bool SW64>
__device__ __forceinline__ uint64_t stage_desc(uint32_t addr) {
    uint32_t lo = ((addr & 0x3FFFFu) >> 4) | ((SW64 ? (8192u >> 4) : (8192u >> 4)) << 16);
    uint32_t hi = (SW64 ? (512u >> 4) : (1024u >> 4)) | ((SW64 ? 2u : 1u) << 30);
    return ((uint64_t)hi << 32) | lo;
}

template <bool SW64>
__device__ __forceinline__ void mma_chunk(float (&acc)[32], const uint32_t (&a)[32][4], Ring& r, int lane) {
    uint32_t prev = 0;
#pragma unroll
    for (int q = 0; q < 4; q++) {
        mbar_wait(r.full0 + r.s * 8, r.ph);
        uint64_t desc = stage_desc<SW64>(r.ring_base + r.s * STAGE_BYTES);
        wgmma_fence();
#pragma unroll
        for (int k = 0; k < 8; k++)
            wgmma_n64(acc, a[q * 8 + k], desc + (uint64_t)(k * (SW64 ? 64 : 128)), (q | k) != 0);
        wgmma_commit();
        if (q > 0) { wgmma_wait<1>(); r.release(prev, lane); }
        prev = r.s;
        r.advance();
    }
    wgmma_wait<0>();
    r.release(prev, lane);
}

__device__ __forceinline__ void load_frags(uint32_t (&a)[32][4], const uint4* src) {
#pragma unroll
    for (int k = 0; k < 32; k++) {
        uint4 v = ldg128(src + k * 128);
        a[k][0] = v.x; a[k][1] = v.y; a[k][2] = v.z; a[k][3] = v.w;
    }
}

__device__ __forceinline__ void center(uint32_t (&a)[32][4], float mean0, float mean1) {
    uint32_t m0 = pack2(mean0, mean0), m1 = pack2(mean1, mean1);
#pragma unroll
    for (int k = 0; k < 32; k++) {
        a[k][0] = hsub2(a[k][0], m0); a[k][1] = hsub2(a[k][1], m1);
        a[k][2] = hsub2(a[k][2], m0); a[k][3] = hsub2(a[k][3], m1);
    }
}

__device__ __forceinline__ void combine_stats(const float4* st, int lane, float& mean0, float& mean1, float& rstd0, float& rstd1) {
    const int g = lane >> 2, t4 = lane & 3;
    float4 p = ldg128f(st + (2 * t4) * 8 + g), q = ldg128f(st + (2 * t4 + 1) * 8 + g);
    float s0 = p.x + q.x, s1 = p.z + q.z;
    s0 += __shfl_xor_sync(~0u, s0, 1); s1 += __shfl_xor_sync(~0u, s1, 1);
    s0 += __shfl_xor_sync(~0u, s0, 2); s1 += __shfl_xor_sync(~0u, s1, 2);
    mean0 = s0 * 0.125f; mean1 = s1 * 0.125f;
    float d0 = p.x - mean0, e0 = q.x - mean0, d1 = p.z - mean1, e1 = q.z - mean1;
    float m0 = p.y + q.y + 64.f * (d0 * d0 + e0 * e0), m1 = p.w + q.w + 64.f * (d1 * d1 + e1 * e1);
    m0 += __shfl_xor_sync(~0u, m0, 1); m1 += __shfl_xor_sync(~0u, m1, 1);
    m0 += __shfl_xor_sync(~0u, m0, 2); m1 += __shfl_xor_sync(~0u, m1, 2);
    rstd0 = rsqrtf(m0 * (1.f / 512.f) + 1e-5f);
    rstd1 = rsqrtf(m1 * (1.f / 512.f) + 1e-5f);
}

__device__ __forceinline__ void residual_epilogue(const float (&acc)[32], const uint32_t (&res)[4][4], uint32_t (&xo)[4][4],
                                                  float4* st_out, int lane, bool want_stats) {
    float v[32];
#pragma unroll
    for (int q = 0; q < 4; q++) {
#pragma unroll
        for (int hh = 0; hh < 2; hh++) {
            const int c = (2 * q + hh) * 4;
            uint32_t r0 = res[q][hh * 2], r1 = res[q][hh * 2 + 1];
            uint32_t o0 = pack2(acc[c] + bf_lo(r0), acc[c + 1] + bf_hi(r0));
            uint32_t o1 = pack2(acc[c + 2] + bf_lo(r1), acc[c + 3] + bf_hi(r1));
            xo[q][hh * 2] = o0; xo[q][hh * 2 + 1] = o1;
            v[c] = bf_lo(o0); v[c + 1] = bf_hi(o0); v[c + 2] = bf_lo(o1); v[c + 3] = bf_hi(o1);
        }
    }
    if (want_stats) {
        float s0 = 0.f, s1 = 0.f;
#pragma unroll
        for (int c = 0; c < 8; c++) { s0 += v[4 * c] + v[4 * c + 1]; s1 += v[4 * c + 2] + v[4 * c + 3]; }
        s0 += __shfl_xor_sync(~0u, s0, 1); s1 += __shfl_xor_sync(~0u, s1, 1);
        s0 += __shfl_xor_sync(~0u, s0, 2); s1 += __shfl_xor_sync(~0u, s1, 2);
        const float m0 = s0 * (1.f / 64.f), m1 = s1 * (1.f / 64.f);
        float q0 = 0.f, q1 = 0.f;
#pragma unroll
        for (int c = 0; c < 8; c++) {
            float a = v[4 * c] - m0, b = v[4 * c + 1] - m0, d = v[4 * c + 2] - m1, e = v[4 * c + 3] - m1;
            q0 += a * a + b * b; q1 += d * d + e * e;
        }
        q0 += __shfl_xor_sync(~0u, q0, 1); q1 += __shfl_xor_sync(~0u, q1, 1);
        q0 += __shfl_xor_sync(~0u, q0, 2); q1 += __shfl_xor_sync(~0u, q1, 2);
        if ((lane & 3) == 0) {
            asm volatile("st.global.v4.f32 [%0], {%1,%2,%3,%4};" :: "l"(st_out + (lane >> 2)), "f"(m0), "f"(q0), "f"(m1), "f"(q1) : "memory");
        }
    }
}

__device__ __forceinline__ void signal_flag(unsigned* f, int lane) {
    __syncwarp();
    if (lane == 0) red_release(f, 1);
}

__global__ void __launch_bounds__(NTHREADS, 1) fused_kernel(const __grid_constant__ Params P) {
    extern __shared__ __align__(1024) uint8_t smem[];
    const uint32_t sbase = smem_u32(smem);
    const uint32_t bar_full = sbase + SM_BAR, bar_empty = bar_full + NST * 8, role_addr = bar_empty + NST * 8;
    const int tid = threadIdx.x, warp = tid >> 5, lane = tid & 31;
    const uint32_t rank = cluster_rank();

    if (tid == 0) {
        if (sbase & 1023u) __trap();
        for (int s = 0; s < NST; s++) { mbar_init(bar_full + s * 8, 1); mbar_init(bar_empty + s * 8, 16); }
        asm volatile("fence.mbarrier_init.release.cluster;" ::: "memory");
    }
    if (tid == 32 && rank == 0) {
        const int gam = P.gpc_of_tpc[sm_id() >> 1] & 7;
        unsigned long long old = atomicAdd(&g_ticket, 1ull << (8 * gam));
        int tk = (int)((old >> (8 * gam)) & 0xFF);
        int role = gam * 8 + tk;
        if (tk >= 8) {
            unsigned long long cur; uint32_t n = 0;
            for (;;) {
                asm volatile("ld.relaxed.gpu.global.u64 %0, [%1];" : "=l"(cur) : "l"(&g_ticket) : "memory");
                int tot = 0;
                for (int g = 0; g < 8; g++) tot += (int)((cur >> (8 * g)) & 0xFF);
                if (tot >= NCLUSTERS) break;
                if (++n > SPIN_LIMIT) __trap();
            }
            int orank = tk - 8;
            for (int g = 0; g < gam; g++) { int c = (int)((cur >> (8 * g)) & 0xFF); if (c > 8) orank += c - 8; }
            role = -1;
            for (int g = 0; g < 8 && role < 0; g++) {
                int c = (int)((cur >> (8 * g)) & 0xFF);
                int fr = c < 8 ? 8 - c : 0;
                if (orank < fr) role = g * 8 + c + orank; else orank -= fr;
            }
        }
        asm volatile("st.shared::cluster.u32 [%0], %1;" :: "r"(mapa(role_addr, 0)), "r"(role) : "memory");
        asm volatile("st.shared::cluster.u32 [%0], %1;" :: "r"(mapa(role_addr, 1)), "r"(role) : "memory");
    }
    if (tid == 64) {
        asm volatile("prefetch.tensormap [%0];" :: "l"(&P.tm_x) : "memory");
        asm volatile("prefetch.tensormap [%0];" :: "l"(&P.tm_qkv) : "memory");
        asm volatile("prefetch.tensormap [%0];" :: "l"(&P.tm_wo) : "memory");
        asm volatile("prefetch.tensormap [%0];" :: "l"(&P.tm_wg) : "memory");
        asm volatile("prefetch.tensormap [%0];" :: "l"(&P.tm_wu) : "memory");
        asm volatile("prefetch.tensormap [%0];" :: "l"(&P.tm_wd) : "memory");
    }
    __syncwarp();
    cluster_arrive();
    cluster_wait();
    int role;
    asm volatile("ld.shared.u32 %0, [%1];" : "=r"(role) : "r"(role_addr) : "memory");
    const int grp = (role >> 3) * 2 + (int)rank;
    const int j = role & 7;

    if (warp >= 8) {
        asm volatile("setmaxnreg.dec.sync.aligned.u32 40;");
        if (warp == 8) {
            if (elect_one()) {
                uint32_t s = 0, ph = 0;
                const uint32_t xring = opaque(sbase + SM_RING), ring = opaque(sbase + SM_RING + rank * 8192u), fb = opaque(bar_full), eb = opaque(bar_empty);
                const int jj = (int)opaque((uint32_t)j), rk = (int)opaque(rank);
#define STAGE_BEGIN() do { mbar_wait(eb + s * 8, ph ^ 1); mbar_expect_tx(fb + s * 8, STAGE_BYTES); } while (0)
#define STAGE_END() do { if (++s == NST) { s = 0; ph ^= 1; } } while (0)
#pragma unroll 1
                for (int u = 0; u < 8; u++) {
                    STAGE_BEGIN();
                    const int xrow = ((u >> 2) * 16 + grp) * 64, xcol = (u & 3) * 128;
                    tma2d(xring + s * STAGE_BYTES, &P.tm_x, fb + s * 8, xcol, xrow);
                    tma2d(xring + s * STAGE_BYTES + 8192, &P.tm_x, fb + s * 8, xcol + 64, xrow);
                    STAGE_END();
                }
#pragma unroll 1
                for (int l = 0; l < 2; l++) {
#pragma unroll 1
                    for (int c = 0; c < 3; c++) {
                        const int col = (c == 0 ? 512 : c == 1 ? 1024 : 0) + 64 * jj;
#pragma unroll 1
                        for (int q = 0; q < 4; q++) {
                            STAGE_BEGIN();
                            tma2d_mc(ring + s * STAGE_BYTES, &P.tm_qkv, fb + s * 8, col, q * 128 + rk * 64);
                            STAGE_END();
                        }
                    }
#pragma unroll 1
                    for (int q = 0; q < 4; q++) {
                        STAGE_BEGIN();
                        tma2d_mc(ring + s * STAGE_BYTES, &P.tm_wo, fb + s * 8, 64 * jj, q * 128 + rk * 64);
                        STAGE_END();
                    }
                    const CUtensorMap* tmu = rk == 0 ? &P.tm_wg : &P.tm_wu;
#pragma unroll 1
                    for (int c = 0; c < 7; c++) {
#pragma unroll 1
                        for (int q = 0; q < 4; q++) {
                            STAGE_BEGIN();
                            tma2d_mc(ring + s * STAGE_BYTES, tmu, fb + s * 8, 224 * jj + 32 * c, q * 128);
                            STAGE_END();
                        }
                    }
#pragma unroll 1
                    for (int q = 0; q < 14; q++) {
                        STAGE_BEGIN();
                        tma2d_mc(ring + s * STAGE_BYTES, &P.tm_wd, fb + s * 8, 64 * jj, q * 128 + rk * 64);
                        STAGE_END();
                    }
                }
            }
            __syncwarp();
        }
        cluster_arrive();
        cluster_wait();
        if (tid == 256 && rank == 0) {
            unsigned old = atomicAdd(&g_done, 1u);
            if (old == NCLUSTERS - 1) {

#pragma unroll 1
 for (int i = 0; i < N_FLAGS; i++) g_flag[i * FLAG_STRIDE] = 0;
                g_ticket = 0ull;
                g_done = 0;
            }
        }
    } else {
        asm volatile("setmaxnreg.inc.sync.aligned.u32 232;");
        const int wg = warp >> 2, w = warp & 3;
        const int t = wg * 16 + grp;
        const int g = lane >> 2, t4 = lane & 3;
        const int tw = w * 32 + lane;
        Ring r;
        r.s = 0; r.ph = 0;
        r.ring_base = sbase + SM_RING; r.full0 = bar_full;
        r.empty_remote = mapa(bar_empty, lane & 1);
        const uint32_t kv_base = sbase + SM_KV + wg * KV_BYTES;
        const int row0 = t * 64 + w * 16 + g;
        unsigned* flags = g_flag;

        uint32_t a[32][4];
        float acc[32];

        TICK(0);
        for (int l = 0; l < 2; l++) {
            const int tb = 1 + l * 20;
            float mean0, mean1, rstd0, rstd1;
            if (l == 0) {
                {
                    const int lr = w * 16 + (lane & 7) + ((lane >> 3) & 1) * 8;
                    const uint32_t rowoff = lr * 128, sw = lr & 7, hi = lane >> 4;
#pragma unroll
                    for (int u = 0; u < 8; u++) {
                        if ((u >> 2) == wg) {
                            mbar_wait(r.full0 + r.s * 8, r.ph);
                            const uint32_t sb = r.ring_base + r.s * STAGE_BYTES + rowoff;
#pragma unroll
                            for (int k = 0; k < 8; k++)
                                ldsm4(a[(u & 3) * 8 + k], sb + (k >> 2) * 8192 + ((((k & 3) * 2 + hi) ^ sw) << 4));
                            __syncwarp();
                        }
                        r.release(r.s, lane);
                        r.advance();
                    }
                }
                float sm[4][4];
#pragma unroll
                for (int c = 0; c < 4; c++) { sm[c][0] = sm[c][1] = sm[c][2] = sm[c][3] = 0.f; }
#pragma unroll
                for (int k = 0; k < 32; k++) mma16816(sm[k & 3], a[k][0], a[k][1], a[k][2], a[k][3], 0x3F803F80u, 0x3F803F80u);
                mean0 = (sm[0][0] + sm[1][0] + sm[2][0] + sm[3][0]) * (1.f / 512.f);
                mean1 = (sm[0][2] + sm[1][2] + sm[2][2] + sm[3][2]) * (1.f / 512.f);
                center(a, mean0, mean1);
                float d0[2][4], d1[2][4];
#pragma unroll
                for (int c = 0; c < 2; c++) { d0[c][0] = d0[c][1] = d0[c][2] = d0[c][3] = 0.f; d1[c][0] = d1[c][1] = d1[c][2] = d1[c][3] = 0.f; }
#pragma unroll
                for (int k = 0; k < 32; k++) {
                    mma16816(d0[k & 1], a[k][0], a[k][1], a[k][2], a[k][3], a[k][0], a[k][2]);
                    mma16816(d1[k & 1], a[k][0], a[k][1], a[k][2], a[k][3], a[k][1], a[k][3]);
                }
                float e0 = (g & 1) ? d0[0][1] + d0[1][1] : d0[0][0] + d0[1][0];
                float e1 = (g & 1) ? d1[0][3] + d1[1][3] : d1[0][2] + d1[1][2];
                const int src = g * 4 + (g >> 1);
                e0 = __shfl_sync(~0u, e0, src); e1 = __shfl_sync(~0u, e1, src);
                const float dl0 = mean0 - bf_lo(pack2(mean0, mean0)), dl1 = mean1 - bf_lo(pack2(mean1, mean1));
                rstd0 = rsqrtf(fmaxf(e0 * (1.f / 512.f) - dl0 * dl0, 0.f) + 1e-5f);
                rstd1 = rsqrtf(fmaxf(e1 * (1.f / 512.f) - dl1 * dl1, 0.f) + 1e-5f);
            } else {
                wait_flag(flags + (FL_X2 + t * 4 + w) * FLAG_STRIDE, 8);
            TICK(tb + 0);
                load_frags(a, g_x2 + (size_t)t * 32 * 128 + tw);
                combine_stats(g_st2 + (t * 4 + w) * 64, lane, mean0, mean1, rstd0, rstd1);
                center(a, mean0, mean1);
            }
TICK(tb + 1);
            uint4* halo_out = g_halo + (size_t)((l * NT + t) * 8 + j) * 256 + lane;
            mma_chunk<false>(acc, a, r, lane);
#pragma unroll
            for (int h = 0; h < 4; h++) {
                uint32_t r0 = pack2(acc[8 * h] * rstd0, acc[8 * h + 1] * rstd0), r1 = pack2(acc[8 * h + 2] * rstd1, acc[8 * h + 3] * rstd1);
                uint32_t r2 = pack2(acc[8 * h + 4] * rstd0, acc[8 * h + 5] * rstd0), r3 = pack2(acc[8 * h + 6] * rstd1, acc[8 * h + 7] * rstd1);
                sts128(kv_base + (w * 8 + h) * 512 + lane * 16, r0, r1, r2, r3);
                if (w == 3) stg128(halo_out + h * 32, r0, r1, r2, r3);
            }
            TICK(tb + 2);
            mma_chunk<false>(acc, a, r, lane);
#pragma unroll
            for (int h = 0; h < 4; h++) {
                uint32_t r0 = pack2(acc[8 * h] * rstd0, acc[8 * h + 1] * rstd0), r1 = pack2(acc[8 * h + 2] * rstd1, acc[8 * h + 3] * rstd1);
                uint32_t r2 = pack2(acc[8 * h + 4] * rstd0, acc[8 * h + 5] * rstd0), r3 = pack2(acc[8 * h + 6] * rstd1, acc[8 * h + 7] * rstd1);
                r0 = movmat(r0); r1 = movmat(r1); r2 = movmat(r2); r3 = movmat(r3);
                sts128(kv_base + (w * 8 + 4 + h) * 512 + lane * 16, r0, r1, r2, r3);
                if (w == 3) stg128(halo_out + (4 + h) * 32, r0, r1, r2, r3);
            }
            if (w == 3) signal_flag(flags + (FL_HALO + t * 8 + j) * FLAG_STRIDE, lane);
            TICK(tb + 3);
            mma_chunk<false>(acc, a, r, lane);
            uint32_t qf[4][4];
            TICK(tb + 4);
#pragma unroll
            for (int h = 0; h < 4; h++) {
                qf[h][0] = pack2(acc[8 * h] * rstd0, acc[8 * h + 1] * rstd0); qf[h][1] = pack2(acc[8 * h + 2] * rstd1, acc[8 * h + 3] * rstd1);
                qf[h][2] = pack2(acc[8 * h + 4] * rstd0, acc[8 * h + 5] * rstd0); qf[h][3] = pack2(acc[8 * h + 6] * rstd1, acc[8 * h + 7] * rstd1);
            }
            named_bar_sync(1 + wg, 128);
            TICK(tb + 19);
            {
                const bool has_prev = (w > 0) || (t > 0);
                const uint4* halo_in = g_halo + (size_t)((l * NT + (t > 0 ? t - 1 : 0)) * 8 + j) * 256 + lane;
                if (w == 0 && t > 0) wait_flag(flags + (FL_HALO + (t - 1) * 8 + j) * FLAG_STRIDE, l + 1);
                const bool hi_t = t4 > (g >> 1);
                const bool odd = g & 1;
                constexpr float SC = 0.25f * 1.4426950408889634f;
                const float NEG = __int_as_float(0xff800000);
#pragma unroll
                for (int h = 0; h < 4; h++) {
                    uint4 kp, vp;
                    if (w > 0) {
                        kp = lds128(kv_base + ((w - 1) * 8 + h) * 512 + lane * 16);
                        vp = lds128(kv_base + ((w - 1) * 8 + 4 + h) * 512 + lane * 16);
                    } else if (t > 0) {
                        kp = ldg128(halo_in + h * 32); vp = ldg128(halo_in + (4 + h) * 32);
                    } else {
                        kp = make_uint4(0, 0, 0, 0); vp = kp;
                    }
                    uint4 ko = lds128(kv_base + (w * 8 + h) * 512 + lane * 16);
                    uint4 vo = lds128(kv_base + (w * 8 + 4 + h) * 512 + lane * 16);
                    float s0[4] = {0, 0, 0, 0}, s1[4] = {0, 0, 0, 0}, s2[4] = {0, 0, 0, 0}, s3[4] = {0, 0, 0, 0};
                    mma16816(s0, qf[h][0], qf[h][1], qf[h][2], qf[h][3], kp.x, kp.z);
                    mma16816(s1, qf[h][0], qf[h][1], qf[h][2], qf[h][3], kp.y, kp.w);
                    mma16816(s2, qf[h][0], qf[h][1], qf[h][2], qf[h][3], ko.x, ko.z);
                    mma16816(s3, qf[h][0], qf[h][1], qf[h][2], qf[h][3], ko.y, ko.w);
                    float t0g = odd ? s0[1] : s0[0], t1g = odd ? s1[1] : s1[0], t2g = odd ? s2[1] : s2[0];
                    float t1h = odd ? s1[3] : s1[2], t2h = odd ? s2[3] : s2[2], t3h = odd ? s3[3] : s3[2];
                    if (!has_prev) { t0g = NEG; t1g = NEG; t1h = NEG; }
                    float eg = hi_t ? t0g : t2g;
                    float eh = hi_t ? t1h : t3h;
                    float mg = fmaxf(eg, t1g), mh = fmaxf(eh, t2h);
                    mg = fmaxf(mg, __shfl_xor_sync(~0u, mg, 1)); mh = fmaxf(mh, __shfl_xor_sync(~0u, mh, 1));
                    mg = fmaxf(mg, __shfl_xor_sync(~0u, mg, 2)); mh = fmaxf(mh, __shfl_xor_sync(~0u, mh, 2));
                    float peg = ex2((eg - mg) * SC), p1g = ex2((t1g - mg) * SC);
                    float peh = ex2((eh - mh) * SC), p2h = ex2((t2h - mh) * SC);
                    float sg = peg + p1g, sh = peh + p2h;
                    sg += __shfl_xor_sync(~0u, sg, 1); sh += __shfl_xor_sync(~0u, sh, 1);
                    sg += __shfl_xor_sync(~0u, sg, 2); sh += __shfl_xor_sync(~0u, sh, 2);
                    const float ig = 1.f / sg, ih = 1.f / sh;
                    peg *= ig; p1g *= ig; peh *= ih; p2h *= ih;
                    const uint32_t sh16 = odd ? 16 : 0;
                    uint32_t beg = (pack2(peg, 0.f) & 0xffffu) << sh16, b1g = (pack2(p1g, 0.f) & 0xffffu) << sh16;
                    uint32_t beh = (pack2(peh, 0.f) & 0xffffu) << sh16, b2h = (pack2(p2h, 0.f) & 0xffffu) << sh16;
                    uint32_t pa0 = hi_t ? beg : 0u, pa3 = hi_t ? beh : 0u;
                    uint32_t pb0 = hi_t ? 0u : beg, pb3 = hi_t ? 0u : beh;
                    float o0[4] = {0, 0, 0, 0}, o1[4] = {0, 0, 0, 0};
                    mma16816(o0, pa0, 0u, b1g, pa3, vp.x, vp.y);
                    mma16816(o1, pa0, 0u, b1g, pa3, vp.z, vp.w);
                    mma16816(o0, pb0, b2h, 0u, pb3, vo.x, vo.y);
                    mma16816(o1, pb0, b2h, 0u, pb3, vo.z, vo.w);
                    stg128(g_o + ((size_t)t * 32 + 4 * j + h) * 128 + tw,
                           pack2(o0[0], o0[1]), pack2(o0[2], o0[3]), pack2(o1[0], o1[1]), pack2(o1[2], o1[3]));
                }
                signal_flag(flags + (FL_O + t * 4 + w) * FLAG_STRIDE, lane);
            }
            TICK(tb + 5);
            uint32_t res[4][4], xo[4][4];
            if (l == 0) {
                const __nv_bfloat16* xr = P.x + (size_t)row0 * DM + 64 * j + 2 * t4;
#pragma unroll
                for (int q = 0; q < 4; q++) {
                    res[q][0] = ldg32(xr + q * 16); res[q][1] = ldg32(xr + 8 * DM + q * 16);
                    res[q][2] = ldg32(xr + q * 16 + 8); res[q][3] = ldg32(xr + 8 * DM + q * 16 + 8);
                }
            } else {
#pragma unroll
                for (int q = 0; q < 4; q++) {
                    uint4 v = ldg128(g_x2 + ((size_t)t * 32 + 4 * j + q) * 128 + tw);
                    res[q][0] = v.x; res[q][1] = v.y; res[q][2] = v.z; res[q][3] = v.w;
                }
            }
            wait_flag(flags + (FL_O + t * 4 + w) * FLAG_STRIDE, 8 * (l + 1));
            TICK(tb + 6);
            load_frags(a, g_o + (size_t)t * 32 * 128 + tw);
            TICK(tb + 7);
            mma_chunk<false>(acc, a, r, lane);
TICK(tb + 8);
            residual_epilogue(acc, res, xo, g_st1 + ((t * 4 + w) * 8 + j) * 8, lane, true);
            TICK(tb + 18);
#pragma unroll
            for (int q = 0; q < 4; q++)
                stg128(g_x1 + ((size_t)t * 32 + 4 * j + q) * 128 + tw, xo[q][0], xo[q][1], xo[q][2], xo[q][3]);
            signal_flag(flags + (FL_X1 + t * 4 + w) * FLAG_STRIDE, lane);
            TICK(tb + 9);
            wait_flag(flags + (FL_X1 + t * 4 + w) * FLAG_STRIDE, 8 * (l + 1));
            TICK(tb + 10);
            load_frags(a, g_x1 + (size_t)t * 32 * 128 + tw);
            combine_stats(g_st1 + (t * 4 + w) * 64, lane, mean0, mean1, rstd0, rstd1);
TICK(tb + 11);
            center(a, mean0, mean1);
            {
                const float q0 = rstd0 * rstd0, q1 = rstd1 * rstd1;
                uint4* hdst = g_h + ((size_t)t * 112 + 14 * j) * 128 + tw;
#pragma unroll 1
                for (int c = 0; c < 7; c++) {
                    mma_chunk<true>(acc, a, r, lane);
#pragma unroll
                    for (int ks = 0; ks < 2; ks++) {
                        const int b = ks * 8;
                        stg128(hdst + (2 * c + ks) * 128,
                               pack2(acc[b] * acc[16 + b] * q0, acc[b + 1] * acc[17 + b] * q0),
                               pack2(acc[b + 2] * acc[18 + b] * q1, acc[b + 3] * acc[19 + b] * q1),
                               pack2(acc[b + 4] * acc[20 + b] * q0, acc[b + 5] * acc[21 + b] * q0),
                               pack2(acc[b + 6] * acc[22 + b] * q1, acc[b + 7] * acc[23 + b] * q1));
                    }
                }
                signal_flag(flags + (FL_H + t * 4 + w) * FLAG_STRIDE, lane);
            }
            TICK(tb + 12);
            wait_flag(flags + (FL_H + t * 4 + w) * FLAG_STRIDE, 8 * (l + 1));
            TICK(tb + 13);
            {
                const uint4* hsrc = g_h + (size_t)t * 112 * 128 + tw;
#pragma unroll
                for (int b = 0; b < 3; b++) {
#pragma unroll
                    for (int k = 0; k < 8; k++) {
                        uint4 v = ldg128(hsrc + (b * 8 + k) * 128);
                        a[b * 8 + k][0] = v.x; a[b * 8 + k][1] = v.y; a[b * 8 + k][2] = v.z; a[b * 8 + k][3] = v.w;
                    }
                }
                uint32_t prev = 0;
#pragma unroll
                for (int q = 0; q < 14; q++) {
                    mbar_wait(r.full0 + r.s * 8, r.ph);
                    uint64_t desc = stage_desc<false>(r.ring_base + r.s * STAGE_BYTES);
                    wgmma_fence();
#pragma unroll
                    for (int k = 0; k < 8; k++)
                        wgmma_n64(acc, a[(q & 3) * 8 + k], desc + (uint64_t)(k * 128), (q | k) != 0);
                    wgmma_commit();
                    if (q > 0) { wgmma_wait<1>(); r.release(prev, lane); }
                    prev = r.s;
                    r.advance();
                    if (q + 3 < 14) {
#pragma unroll
                        for (int k = 0; k < 8; k++) {
                            uint4 v = ldg128(hsrc + ((q + 3) * 8 + k) * 128);
                            const int b = ((q + 3) & 3) * 8 + k;
                            a[b][0] = v.x; a[b][1] = v.y; a[b][2] = v.z; a[b][3] = v.w;
                        }
                    }
                    if (q == 12) {
#pragma unroll
                        for (int qq = 0; qq < 4; qq++) {
                            uint4 v = ldg128(g_x1 + ((size_t)t * 32 + 4 * j + qq) * 128 + tw);
                            res[qq][0] = v.x; res[qq][1] = v.y; res[qq][2] = v.z; res[qq][3] = v.w;
                        }
                    }
                }
                wgmma_wait<0>();
                r.release(prev, lane);
            }
TICK(tb + 14);
            residual_epilogue(acc, res, xo, g_st2 + ((t * 4 + w) * 8 + j) * 8, lane, l == 0);
            TICK(tb + 16);
            if (l == 0) {
#pragma unroll
                for (int q = 0; q < 4; q++)
                    stg128(g_x2 + ((size_t)t * 32 + 4 * j + q) * 128 + tw, xo[q][0], xo[q][1], xo[q][2], xo[q][3]);
                TICK(tb + 17);
                signal_flag(flags + (FL_X2 + t * 4 + w) * FLAG_STRIDE, lane);
            } else {
                __nv_bfloat16* o = P.out + (size_t)row0 * DM + 64 * j + 2 * t4;
#pragma unroll
                for (int q = 0; q < 4; q++) {
                    *(uint32_t*)(o + q * 16) = xo[q][0]; *(uint32_t*)(o + 8 * DM + q * 16) = xo[q][1];
                    *(uint32_t*)(o + q * 16 + 8) = xo[q][2]; *(uint32_t*)(o + 8 * DM + q * 16 + 8) = xo[q][3];
                }
            }
            TICK(tb + 15);
        }
        cluster_arrive();
        cluster_wait();
    }
}

typedef CUresult (*EncodeFn)(CUtensorMap*, CUtensorMapDataType, cuuint32_t, void*, const cuuint64_t*, const cuuint64_t*,
                             const cuuint32_t*, const cuuint32_t*, CUtensorMapInterleave, CUtensorMapSwizzle,
                             CUtensorMapL2promotion, CUtensorMapFloatOOBfill);

void encode_2d(EncodeFn enc, CUtensorMap* tm, const void* ptr, uint64_t cols, uint64_t rows, uint32_t box_c, uint32_t box_r, CUtensorMapSwizzle sw) {
    cuuint64_t dims[2] = {cols, rows};
    cuuint64_t strides[1] = {cols * 2};
    cuuint32_t box[2] = {box_c, box_r};
    cuuint32_t es[2] = {1, 1};
    enc(tm, CU_TENSOR_MAP_DATA_TYPE_BFLOAT16, 2, const_cast<void*>(ptr), dims, strides, box, es, CU_TENSOR_MAP_INTERLEAVE_NONE, sw,
        CU_TENSOR_MAP_L2_PROMOTION_L2_128B, CU_TENSOR_MAP_FLOAT_OOB_FILL_NONE);
}

void build_gpc_table(unsigned char* table) {
    int M[10] = {0};
    bool ok = true;
    for (int c = 1; c <= 8 && ok; c++) {
        cudaLaunchConfig_t cfg = {};
        cfg.gridDim = dim3(2 * c); cfg.blockDim = dim3(NTHREADS); cfg.dynamicSmemBytes = SM_TOTAL;
        cudaLaunchAttribute at[1];
        at[0].id = cudaLaunchAttributeClusterDimension; at[0].val.clusterDim.x = 2 * c; at[0].val.clusterDim.y = 1; at[0].val.clusterDim.z = 1;
        cfg.attrs = at; cfg.numAttrs = 1;
        if (cudaOccupancyMaxActiveClusters(&M[c], fused_kernel, &cfg) != cudaSuccess) { ok = false; (void)cudaGetLastError(); }
    }
    int n[10] = {0};
    bool found = false;
    if (ok) {
        for (int n9 = 0; n9 <= 8 && !found; n9++) for (int n8 = 0; n8 + n9 <= 8 && !found; n8++)
        for (int n7 = 0; n7 + n8 + n9 <= 8 && !found; n7++) for (int n6 = 0; n6 + n7 + n8 + n9 <= 8 && !found; n6++)
        for (int n5 = 0; n5 + n6 + n7 + n8 + n9 <= 8 && !found; n5++) for (int n4 = 0; n4 + n5 + n6 + n7 + n8 + n9 <= 8 && !found; n4++)
        for (int n3 = 0; n3 + n4 + n5 + n6 + n7 + n8 + n9 <= 8 && !found; n3++)
        for (int n2 = 0; n2 + n3 + n4 + n5 + n6 + n7 + n8 + n9 <= 8 && !found; n2++) {
            int cnt[10] = {0, 0, n2, n3, n4, n5, n6, n7, n8, n9};
            int tot = 0; for (int T = 2; T <= 9; T++) tot += T * cnt[T];
            cnt[1] = M[1] - tot;
            if (cnt[1] < 0) continue;
            bool match = true;
            for (int c = 2; c <= 8 && match; c++) { int m = 0; for (int T = 1; T <= 9; T++) m += cnt[T] * (T / c); match = (m == M[c]); }
            if (match) { for (int T = 1; T <= 9; T++) n[T] = cnt[T]; found = true; }
        }
    }
    for (int i = 0; i < 80; i++) table[i] = (unsigned char)(i & 7);
    if (!found) return;
    int size[8], ng = 0;
    for (int T = 2; T <= 9; T++) for (int k = 0; k < n[T] && ng < 8; k++) size[ng++] = T;
    int id = 0, fill[8] = {0};
    for (int rnd = 0; rnd < 9; rnd++) for (int gI = 0; gI < ng; gI++) if (size[gI] > rnd && id < 80) { table[id++] = (unsigned char)gI; fill[gI]++; }
    for (int k = 0; k < n[1] && id < 80; k++) {
        int best = 0; for (int gI = 1; gI < 8; gI++) if (fill[gI] < fill[best]) best = gI;
        table[id++] = (unsigned char)best; fill[best]++;
    }
}

}

extern "C" void kernel_launch(void* const* d_in, const int* in_sizes, int n_in, void* d_out, int out_size) {
    (void)in_sizes; (void)n_in; (void)out_size;
    static Params P;
    static bool init = false;
    static const void* cached[8] = {nullptr};
    bool same = init;
    for (int i = 0; i < 7 && same; i++) same = (cached[i] == d_in[i]);
    same = same && cached[7] == d_out;
    if (!same) {
        void* fn = nullptr;
        cudaDriverEntryPointQueryResult st;
        cudaGetDriverEntryPoint("cuTensorMapEncodeTiled", &fn, cudaEnableDefault, &st);
        EncodeFn enc = (EncodeFn)fn;
        const void* wqkv = d_in[1]; const void* wo = d_in[2];
        const void* wg = d_in[4]; const void* wu = d_in[5]; const void* wd = d_in[6];
        encode_2d(enc, &P.tm_x, d_in[0], 512, 2048, 64, 64, CU_TENSOR_MAP_SWIZZLE_128B);
        encode_2d(enc, &P.tm_qkv, wqkv, 1536, 512, 64, 64, CU_TENSOR_MAP_SWIZZLE_128B);
        encode_2d(enc, &P.tm_wo, wo, 512, 512, 64, 64, CU_TENSOR_MAP_SWIZZLE_128B);
        encode_2d(enc, &P.tm_wg, wg, 1792, 512, 32, 128, CU_TENSOR_MAP_SWIZZLE_64B);
        encode_2d(enc, &P.tm_wu, wu, 1792, 512, 32, 128, CU_TENSOR_MAP_SWIZZLE_64B);
        encode_2d(enc, &P.tm_wd, wd, 512, 1792, 64, 64, CU_TENSOR_MAP_SWIZZLE_128B);
        P.x = (const __nv_bfloat16*)d_in[0];
        P.out = (__nv_bfloat16*)d_out;
        if (!init) {
            cudaFuncSetAttribute(fused_kernel, cudaFuncAttributeMaxDynamicSharedMemorySize, SM_TOTAL);
            cudaFuncSetAttribute(fused_kernel, cudaFuncAttributeNonPortableClusterSizeAllowed, 1);
            build_gpc_table(P.gpc_of_tpc);
        }
        for (int i = 0; i < 7; i++) cached[i] = d_in[i];
        cached[7] = d_out;
        init = true;
    }
    cudaLaunchConfig_t cfg = {};
    cfg.gridDim = dim3(2 * NCLUSTERS); cfg.blockDim = dim3(NTHREADS); cfg.dynamicSmemBytes = SM_TOTAL;
    cfg.stream = cudaStreamPerThread;
    cudaLaunchAttribute at[1];
    at[0].id = cudaLaunchAttributeClusterDimension; at[0].val.clusterDim.x = 2; at[0].val.clusterDim.y = 1; at[0].val.clusterDim.z = 1;
    cfg.attrs = at; cfg.numAttrs = 1;
    cudaLaunchKernelEx(&cfg, fused_kernel, P);
}
```

```cpp
#include <cuda_runtime.h>
#include <cuda_bf16.h>
#include <cuda.h>
#include <stdint.h>

namespace {

constexpr int DM = 512;
constexpr int NT = 32;
constexpr int NST = 10;
constexpr int STAGE_BYTES = 16384;
constexpr int XST = NST - 4;
constexpr int ASLOT = 4096;
constexpr int SM_RING = 0;
constexpr int SM_STG = NST * STAGE_BYTES;
constexpr int SM_BAR = SM_STG + 8 * 2 * ASLOT;
constexpr int SM_TOTAL = SM_BAR + 512;
constexpr int NTHREADS = 384;
constexpr int NCLUSTERS = 64;

constexpr uint32_t X_O = 0;
constexpr uint32_t X_X1 = X_O + NT * 32 * 128;
constexpr uint32_t X_X2 = X_X1 + NT * 32 * 128;
constexpr uint32_t X_H = X_X2 + NT * 32 * 128;
constexpr uint32_t X_P = X_H + NT * 4 * 7 * 2 * 256;
constexpr uint32_t X_ST1 = X_P + NT * 4 * 8 * 128;
constexpr uint32_t X_ST2 = X_ST1 + NT * 4 * 8 * 8;
constexpr uint32_t X_HALO = X_ST2 + NT * 4 * 8 * 8;
constexpr uint32_t X_END = X_HALO + 2 * NT * 8 * 8 * 32;
__device__ uint4 g_x[X_END];
__device__ unsigned g_epoch[NCLUSTERS * 8];
__device__ unsigned g_started[NCLUSTERS * 8];
__device__ unsigned long long g_ticket;
__device__ unsigned g_done;

struct Params {
    CUtensorMap tm_x;
    CUtensorMap tm_qkv;
    CUtensorMap tm_wo;
    CUtensorMap tm_wg;
    CUtensorMap tm_wu;
    CUtensorMap tm_wd;
    const __nv_bfloat16* x;
    __nv_bfloat16* out;
    const uint8_t* pf_ptr[5];
    unsigned pf_bytes[5];
    int static_roles;
    signed char role_of_tpc[72];
};

__device__ __forceinline__ uint32_t smem_u32(const void* p) { return (uint32_t)__cvta_generic_to_shared(p); }
__device__ __forceinline__ uint32_t opaque(uint32_t x) { uint32_t y; asm volatile("mov.u32 %0, %1;" : "=r"(y) : "r"(x)); return y; }
__device__ __forceinline__ uint32_t uniform(uint32_t x) {
    uint32_t y; asm volatile("shfl.sync.idx.b32 %0, %1, 0, 0x1f, 0xffffffff;" : "=r"(y) : "r"(x)); return y;
}
__device__ __forceinline__ bool elect_one() {
    uint32_t p;
    asm volatile("{\n.reg .pred P;\nelect.sync _|P, 0xffffffff;\nselp.u32 %0, 1, 0, P;\n}" : "=r"(p));
    return p != 0;
}
__device__ __forceinline__ void mbar_init(uint32_t bar, uint32_t count) {
    asm volatile("mbarrier.init.shared::cta.b64 [%0], %1;" :: "r"(bar), "r"(count) : "memory");
}
__device__ __forceinline__ void mbar_expect_tx(uint32_t bar, uint32_t bytes) {
    asm volatile("mbarrier.arrive.expect_tx.shared::cta.b64 _, [%0], %1;" :: "r"(bar), "r"(bytes) : "memory");
}
__device__ __forceinline__ void mbar_arrive_cluster(uint32_t cluster_addr) {
    asm volatile("mbarrier.arrive.shared::cluster.b64 _, [%0];" :: "r"(cluster_addr) : "memory");
}
__device__ __forceinline__ uint32_t mapa(uint32_t addr, uint32_t cta) {
    uint32_t r;
    asm volatile("mapa.shared::cluster.u32 %0, %1, %2;" : "=r"(r) : "r"(addr), "r"(cta));
    return r;
}
__device__ __forceinline__ void mbar_wait(uint32_t bar, uint32_t parity) {
    asm volatile("{\n.reg .pred p;\n.reg .u32 n;\n"
                 "mbarrier.try_wait.parity.shared::cta.b64 p, [%0], %1;\n@p bra DONE_%=;\nmov.u32 n, 0;\n"
                 "WAIT_%=:\nmbarrier.try_wait.parity.shared::cta.b64 p, [%0], %1;\n@p bra DONE_%=;\n"
                 "add.u32 n, n, 1;\nsetp.lt.u32 p, n, 4194304;\n@p bra WAIT_%=;\ntrap;\nDONE_%=:\n}"
                 :: "r"(bar), "r"(parity) : "memory");
}
__device__ __forceinline__ void tma2d_mc(uint32_t dst, const CUtensorMap* tm, uint32_t bar, int c0, int c1) {
    asm volatile("cp.async.bulk.tensor.2d.shared::cluster.global.mbarrier::complete_tx::bytes.multicast::cluster [%0], [%1, {%3, %4}], [%2], %5;"
                 :: "r"(dst), "l"(tm), "r"(bar), "r"(c0), "r"(c1), "h"((uint16_t)3) : "memory");
}
__device__ __forceinline__ void tma3d_mc(uint32_t dst, const CUtensorMap* tm, uint32_t bar, int c0, int c1, int c2) {
    asm volatile("cp.async.bulk.tensor.3d.shared::cluster.global.mbarrier::complete_tx::bytes.multicast::cluster [%0], [%1, {%3, %4, %5}], [%2], %6;"
                 :: "r"(dst), "l"(tm), "r"(bar), "r"(c0), "r"(c1), "r"(c2), "h"((uint16_t)3) : "memory");
}
__device__ __forceinline__ void tma3d(uint32_t dst, const CUtensorMap* tm, uint32_t bar, int c0, int c1, int c2) {
    asm volatile("cp.async.bulk.tensor.3d.shared::cluster.global.mbarrier::complete_tx::bytes [%0], [%1, {%3, %4, %5}], [%2];"
                 :: "r"(dst), "l"(tm), "r"(bar), "r"(c0), "r"(c1), "r"(c2) : "memory");
}
__device__ __forceinline__ void bulk_g2s(uint32_t dst, const void* src, uint32_t bytes, uint32_t bar) {
    asm volatile("cp.async.bulk.shared::cluster.global.mbarrier::complete_tx::bytes [%0], [%1], %2, [%3];"
                 :: "r"(dst), "l"(src), "r"(bytes), "r"(bar) : "memory");
}
__device__ __forceinline__ void ldsm4(uint32_t (&a)[4], uint32_t addr) {
    asm volatile("ldmatrix.sync.aligned.m8n8.x4.shared.b16 {%0,%1,%2,%3}, [%4];"
                 : "=r"(a[0]), "=r"(a[1]), "=r"(a[2]), "=r"(a[3]) : "r"(addr) : "memory");
}
__device__ __forceinline__ void cluster_arrive() { asm volatile("barrier.cluster.arrive.release.aligned;" ::: "memory"); }
__device__ __forceinline__ void cluster_wait() { asm volatile("barrier.cluster.wait.acquire.aligned;" ::: "memory"); }
__device__ __forceinline__ uint32_t cluster_rank() { uint32_t r; asm volatile("mov.u32 %0, %%cluster_ctarank;" : "=r"(r)); return r; }
__device__ __forceinline__ uint32_t sm_id() { uint32_t r; asm volatile("mov.u32 %0, %%smid;" : "=r"(r)); return r; }
__device__ __forceinline__ void named_bar_sync(int id, int n) { asm volatile("bar.sync %0, %1;" :: "r"(id), "r"(n) : "memory"); }
__device__ __forceinline__ void named_bar_arrive(int id, int n) { asm volatile("bar.arrive %0, %1;" :: "r"(id), "r"(n) : "memory"); }

__device__ __forceinline__ void ldx_strong(uint32_t (&v)[4], const uint4* p) {
    asm volatile("ld.relaxed.gpu.global.v4.u32 {%0,%1,%2,%3}, [%4];" : "=r"(v[0]), "=r"(v[1]), "=r"(v[2]), "=r"(v[3]) : "l"(p) : "memory");
}
__device__ __forceinline__ unsigned ld_relaxed(const unsigned* p) {
    unsigned v; asm volatile("ld.relaxed.gpu.global.u32 %0, [%1];" : "=r"(v) : "l"(p) : "memory"); return v;
}
__device__ __forceinline__ void stx(uint4* p, uint32_t a, uint32_t b, uint32_t c, uint32_t d, uint32_t tag) {
    asm volatile("st.global.v4.u32 [%0], {%1,%2,%3,%4};" :: "l"(p), "r"((a & ~1u) | tag), "r"(b), "r"(c), "r"(d) : "memory");
}
__device__ __forceinline__ void sts128(uint32_t addr, uint32_t a, uint32_t b, uint32_t c, uint32_t d) {
    asm volatile("st.shared.v4.u32 [%0], {%1,%2,%3,%4};" :: "r"(addr), "r"(a), "r"(b), "r"(c), "r"(d) : "memory");
}
__device__ __forceinline__ void lds128(uint32_t (&v)[4], uint32_t addr) {
    asm volatile("ld.shared.v4.u32 {%0,%1,%2,%3}, [%4];" : "=r"(v[0]), "=r"(v[1]), "=r"(v[2]), "=r"(v[3]) : "r"(addr) : "memory");
}
__device__ __forceinline__ void lds128_re(uint32_t (&v)[4], uint32_t addr) {
    asm volatile("ld.shared.v4.u32 {%0,%1,%2,%3}, [%4];" : "+r"(v[0]), "+r"(v[1]), "+r"(v[2]), "+r"(v[3]) : "r"(addr) : "memory");
}
__device__ __forceinline__ uint32_t lds32(uint32_t addr) {
    uint32_t v; asm volatile("ld.shared.u32 %0, [%1];" : "=r"(v) : "r"(addr) : "memory"); return v;
}
__device__ __forceinline__ uint32_t pack2(float lo, float hi) {
    uint32_t r; asm("cvt.rn.bf16x2.f32 %0, %1, %2;" : "=r"(r) : "f"(hi), "f"(lo)); return r;
}
__device__ __forceinline__ float bf_lo(uint32_t u) { return __uint_as_float(u << 16); }
__device__ __forceinline__ float bf_hi(uint32_t u) { return __uint_as_float(u & 0xffff0000u); }
__device__ __forceinline__ uint32_t hsub2(uint32_t a, uint32_t b) {
    uint32_t r; asm("sub.rn.bf16x2 %0, %1, %2;" : "=r"(r) : "r"(a), "r"(b)); return r;
}
__device__ __forceinline__ uint32_t movmat(uint32_t a) {
    uint32_t d; asm volatile("movmatrix.sync.aligned.m8n8.trans.b16 %0, %1;" : "=r"(d) : "r"(a)); return d;
}
__device__ __forceinline__ void mma16816(float (&d)[4], uint32_t a0, uint32_t a1, uint32_t a2, uint32_t a3, uint32_t b0, uint32_t b1) {
    asm volatile("mma.sync.aligned.m16n8k16.row.col.f32.bf16.bf16.f32 {%0,%1,%2,%3}, {%4,%5,%6,%7}, {%8,%9}, {%0,%1,%2,%3};"
                 : "+f"(d[0]), "+f"(d[1]), "+f"(d[2]), "+f"(d[3]) : "r"(a0), "r"(a1), "r"(a2), "r"(a3), "r"(b0), "r"(b1));
}
__device__ __forceinline__ float ex2(float x) { float y; asm("ex2.approx.ftz.f32 %0, %1;" : "=f"(y) : "f"(x)); return y; }
__device__ __forceinline__ void spin_guard(uint32_t& n) {
    ++n;
    asm volatile("{\n.reg .pred p;\nsetp.gt.u32 p, %0, 4194304;\n@p trap;\n}" :: "r"(n));
}

__device__ __forceinline__ void wgmma_fence() { asm volatile("wgmma.fence.sync.aligned;" ::: "memory"); }
__device__ __forceinline__ void wgmma_commit() { asm volatile("wgmma.commit_group.sync.aligned;" ::: "memory"); }
template <int N> __device__ __forceinline__ void wgmma_wait() { asm volatile("wgmma.wait_group.sync.aligned %0;" :: "n"(N) : "memory"); }

__device__ __forceinline__ void fence_acc(float (&d)[32]) {
    asm volatile("" : "+f"(d[0]), "+f"(d[1]), "+f"(d[2]), "+f"(d[3]), "+f"(d[4]), "+f"(d[5]), "+f"(d[6]), "+f"(d[7]),
                      "+f"(d[8]), "+f"(d[9]), "+f"(d[10]), "+f"(d[11]), "+f"(d[12]), "+f"(d[13]), "+f"(d[14]), "+f"(d[15]),
                      "+f"(d[16]), "+f"(d[17]), "+f"(d[18]), "+f"(d[19]), "+f"(d[20]), "+f"(d[21]), "+f"(d[22]), "+f"(d[23]),
                      "+f"(d[24]), "+f"(d[25]), "+f"(d[26]), "+f"(d[27]), "+f"(d[28]), "+f"(d[29]), "+f"(d[30]), "+f"(d[31])
                 :: "memory");
}

template <bool ACC>
__device__ __forceinline__ void wgmma_n64(float (&d)[32], const uint32_t (&a)[4], uint32_t dlo, uint32_t dhi) {
    asm volatile("{\n.reg .b64 dsc;\nmov.b64 dsc, {%36, %37};\n"
        "wgmma.mma_async.sync.aligned.m64n64k16.f32.bf16.bf16 "
        "{%0, %1, %2, %3, %4, %5, %6, %7, %8, %9, %10, %11, %12, %13, %14, %15, "
        "%16, %17, %18, %19, %20, %21, %22, %23, %24, %25, %26, %27, %28, %29, %30, %31}, "
        "{%32, %33, %34, %35}, dsc, %38, 1, 1, 1;\n}\n"
        : "+f"(d[0]), "+f"(d[1]), "+f"(d[2]), "+f"(d[3]), "+f"(d[4]), "+f"(d[5]), "+f"(d[6]), "+f"(d[7]),
          "+f"(d[8]), "+f"(d[9]), "+f"(d[10]), "+f"(d[11]), "+f"(d[12]), "+f"(d[13]), "+f"(d[14]), "+f"(d[15]),
          "+f"(d[16]), "+f"(d[17]), "+f"(d[18]), "+f"(d[19]), "+f"(d[20]), "+f"(d[21]), "+f"(d[22]), "+f"(d[23]),
          "+f"(d[24]), "+f"(d[25]), "+f"(d[26]), "+f"(d[27]), "+f"(d[28]), "+f"(d[29]), "+f"(d[30]), "+f"(d[31])
        : "r"(a[0]), "r"(a[1]), "r"(a[2]), "r"(a[3]), "r"(dlo), "r"(dhi), "n"(ACC ? 1 : 0));
}

template <bool ACC>
__device__ __forceinline__ void wgmma_n128(float (&d)[64], const uint32_t (&a)[4], uint32_t dlo, uint32_t dhi) {
    asm volatile("{\n.reg .b64 dsc;\nmov.b64 dsc, {%68, %69};\n"
        "wgmma.mma_async.sync.aligned.m64n128k16.f32.bf16.bf16 "
        "{%0, %1, %2, %3, %4, %5, %6, %7, %8, %9, %10, %11, %12, %13, %14, %15, %16, %17, %18, %19, %20, %21, %22, %23, %24, %25, %26, %27, %28, %29, %30, %31, %32, %33, %34, %35, %36, %37, %38, %39, %40, %41, %42, %43, %44, %45, %46, %47, %48, %49, %50, %51, %52, %53, %54, %55, %56, %57, %58, %59, %60, %61, %62, %63}, "
        "{%64, %65, %66, %67}, dsc, %70, 1, 1, 1;\n}\n"
        : "+f"(d[0]), "+f"(d[1]), "+f"(d[2]), "+f"(d[3]), "+f"(d[4]), "+f"(d[5]), "+f"(d[6]), "+f"(d[7]), "+f"(d[8]), "+f"(d[9]), "+f"(d[10]), "+f"(d[11]), "+f"(d[12]), "+f"(d[13]), "+f"(d[14]), "+f"(d[15]), "+f"(d[16]), "+f"(d[17]), "+f"(d[18]), "+f"(d[19]), "+f"(d[20]), "+f"(d[21]), "+f"(d[22]), "+f"(d[23]), "+f"(d[24]), "+f"(d[25]), "+f"(d[26]), "+f"(d[27]), "+f"(d[28]), "+f"(d[29]), "+f"(d[30]), "+f"(d[31]), "+f"(d[32]), "+f"(d[33]), "+f"(d[34]), "+f"(d[35]), "+f"(d[36]), "+f"(d[37]), "+f"(d[38]), "+f"(d[39]), "+f"(d[40]), "+f"(d[41]), "+f"(d[42]), "+f"(d[43]), "+f"(d[44]), "+f"(d[45]), "+f"(d[46]), "+f"(d[47]), "+f"(d[48]), "+f"(d[49]), "+f"(d[50]), "+f"(d[51]), "+f"(d[52]), "+f"(d[53]), "+f"(d[54]), "+f"(d[55]), "+f"(d[56]), "+f"(d[57]), "+f"(d[58]), "+f"(d[59]), "+f"(d[60]), "+f"(d[61]), "+f"(d[62]), "+f"(d[63])
        : "r"(a[0]), "r"(a[1]), "r"(a[2]), "r"(a[3]), "r"(dlo), "r"(dhi), "n"(ACC ? 1 : 0));
}
__device__ __forceinline__ void fence_acc64(float (&d)[64]) {
    asm volatile("" : "+f"(d[0]), "+f"(d[1]), "+f"(d[2]), "+f"(d[3]), "+f"(d[4]), "+f"(d[5]), "+f"(d[6]), "+f"(d[7]), "+f"(d[8]), "+f"(d[9]), "+f"(d[10]), "+f"(d[11]), "+f"(d[12]), "+f"(d[13]), "+f"(d[14]), "+f"(d[15]), "+f"(d[16]), "+f"(d[17]), "+f"(d[18]), "+f"(d[19]), "+f"(d[20]), "+f"(d[21]), "+f"(d[22]), "+f"(d[23]), "+f"(d[24]), "+f"(d[25]), "+f"(d[26]), "+f"(d[27]), "+f"(d[28]), "+f"(d[29]), "+f"(d[30]), "+f"(d[31]), "+f"(d[32]), "+f"(d[33]), "+f"(d[34]), "+f"(d[35]), "+f"(d[36]), "+f"(d[37]), "+f"(d[38]), "+f"(d[39]), "+f"(d[40]), "+f"(d[41]), "+f"(d[42]), "+f"(d[43]), "+f"(d[44]), "+f"(d[45]), "+f"(d[46]), "+f"(d[47]), "+f"(d[48]), "+f"(d[49]), "+f"(d[50]), "+f"(d[51]), "+f"(d[52]), "+f"(d[53]), "+f"(d[54]), "+f"(d[55]), "+f"(d[56]), "+f"(d[57]), "+f"(d[58]), "+f"(d[59]), "+f"(d[60]), "+f"(d[61]), "+f"(d[62]), "+f"(d[63]) :: "memory");
}

template <bool B> struct BoolC { static constexpr bool value = B; };
template <int N> struct IntC { static constexpr int value = N; };

struct Ring {
    uint32_t s, ph;
    uint32_t rs;
    uint32_t desc0;
    uint32_t full0;
    uint32_t empty_remote;
    bool rel_lane;
    __device__ __forceinline__ void advance() { if (++s == NST) { s = 0; ph ^= 1; } }
    __device__ __forceinline__ void release() {
        if (rel_lane) mbar_arrive_cluster(empty_remote + rs * 8);
        if (++rs == NST) rs = 0;
    }
};

struct AStream {
    uint32_t slot0;
    uint32_t bar0;
    uint32_t ph;
    __device__ __forceinline__ void issue(uint32_t s, uint32_t off, bool go, uint32_t bytes = ASLOT) {
        if (go) {
            const uint4* p = g_x + off;
            if (elect_one()) { mbar_expect_tx(bar0 + s * 8, bytes); bulk_g2s(slot0 + s * ASLOT, p, bytes, bar0 + s * 8); }
            __syncwarp();
        }
    }
    __device__ __forceinline__ void wait(uint32_t s) { mbar_wait(bar0 + s * 8, (ph >> s) & 1); ph ^= 1u << s; }
    __device__ __forceinline__ void validate(uint32_t s, uint32_t off, uint32_t tag, uint32_t lane, bool half = false) {
        const uint32_t p = slot0 + s * ASLOT + lane * 16;
        const uint32_t hmask = half ? 0u : 1u;
        uint32_t n = 0;
        for (;;) {
            wait(s);
            uint32_t bad = 0;
#pragma unroll
            for (int k = 0; k < 4; k++) bad |= lds32(p + k * 512) ^ tag;
            uint32_t bad2 = 0;
#pragma unroll
            for (int k = 4; k < 8; k++) bad2 |= lds32(p + k * 512) ^ tag;
            if (__reduce_or_sync(~0u, (bad & 1) | (bad2 & hmask)) == 0) break;
            spin_guard(n);
            issue(s, off, true, half ? ASLOT / 2 : ASLOT);
        }
    }
    __device__ __forceinline__ void issue_q(uint32_t u, uint32_t off, bool go) {
        if (go) {
            const uint4* p = g_x + off;
            if (elect_one()) { mbar_expect_tx(bar0 + u * 8, 2048); bulk_g2s(slot0 + u * 2048, p, 2048, bar0 + u * 8); }
            __syncwarp();
        }
    }
};

constexpr uint32_t DELAY_O = 650, DELAY_X = 1250;
__device__ __forceinline__ void delay_cycles(uint32_t d) {
    const uint32_t c0 = (uint32_t)clock();
    while ((uint32_t)clock() - c0 < d) {}
}

__device__ __forceinline__ void probe(const uint4* p, uint32_t tag) {
    uint32_t v[1], n = 0;
#pragma unroll
    for (int k = 0; k < 1; k++) v[k] = ld_relaxed((const unsigned*)p);
    for (;;) {
        bool done = false;
#pragma unroll
        for (int k = 0; k < 1; k++) {
            if (!done) {
                if (__reduce_or_sync(~0u, (v[k] ^ tag) & 1) == 0) done = true;
                else v[k] = ld_relaxed((const unsigned*)p);
            }
        }
        if (done) break;
        spin_guard(n);
    }
}

__device__ __forceinline__ void fetch_stats(const uint4* st, uint32_t tag, uint32_t lane, uint32_t keep,
                                            float& mean0, float& mean1, float& rstd0, float& rstd1) {
    const uint4* sp = st + (2 * (lane & 3)) * 8 + (lane >> 2);
    uint32_t p[4], q[4], n = 0;
    for (;;) {
        ldx_strong(p, sp); ldx_strong(q, sp + 8);
        if (__reduce_or_sync(~0u, ((p[0] ^ tag) | (q[0] ^ tag)) & 1) == 0) break;
        spin_guard(n);
    }
    p[0] &= keep; q[0] &= keep;
    const float pm0 = __uint_as_float(p[0]), pq0 = __uint_as_float(p[1]), pm1 = __uint_as_float(p[2]), pq1 = __uint_as_float(p[3]);
    const float qm0 = __uint_as_float(q[0]), qq0 = __uint_as_float(q[1]), qm1 = __uint_as_float(q[2]), qq1 = __uint_as_float(q[3]);
    float s0 = pm0 + qm0, s1 = pm1 + qm1;
    s0 += __shfl_xor_sync(~0u, s0, 1); s1 += __shfl_xor_sync(~0u, s1, 1);
    s0 += __shfl_xor_sync(~0u, s0, 2); s1 += __shfl_xor_sync(~0u, s1, 2);
    mean0 = s0 * 0.125f; mean1 = s1 * 0.125f;
    const float d0 = pm0 - mean0, e0 = qm0 - mean0, d1 = pm1 - mean1, e1 = qm1 - mean1;
    float m0 = pq0 + qq0 + 64.f * (d0 * d0 + e0 * e0), m1 = pq1 + qq1 + 64.f * (d1 * d1 + e1 * e1);
    m0 += __shfl_xor_sync(~0u, m0, 1); m1 += __shfl_xor_sync(~0u, m1, 1);
    m0 += __shfl_xor_sync(~0u, m0, 2); m1 += __shfl_xor_sync(~0u, m1, 2);
    rstd0 = rsqrtf(m0 * (1.f / 512.f) + 1e-5f);
    rstd1 = rsqrtf(m1 * (1.f / 512.f) + 1e-5f);
}

__device__ __forceinline__ void center(uint32_t (&a)[32][4], float mean0, float mean1) {
    const uint32_t m0 = pack2(mean0, mean0), m1 = pack2(mean1, mean1);
#pragma unroll
    for (int k = 0; k < 32; k++) {
        a[k][0] = hsub2(a[k][0], m0); a[k][1] = hsub2(a[k][1], m1);
        a[k][2] = hsub2(a[k][2], m0); a[k][3] = hsub2(a[k][3], m1);
    }
}

__device__ __forceinline__ void publish_x(uint32_t (&xo)[4][4], uint4* x_out, uint4* st_out, int lane, uint32_t tag, uint32_t vbit) {
#pragma unroll
    for (int q = 0; q < 4; q++) {
        xo[q][0] = (xo[q][0] & ~1u) | vbit;
        stx(x_out + q * 32, xo[q][0], xo[q][1], xo[q][2], xo[q][3], tag);
    }
    const float c0 = __shfl_sync(~0u, bf_lo(xo[0][0]), lane & ~3), c1 = __shfl_sync(~0u, bf_lo(xo[0][1]), lane & ~3);
    float s0 = 0.f, s1 = 0.f, q0 = 0.f, q1 = 0.f;
#pragma unroll
    for (int q = 0; q < 4; q++) {
        float a = bf_lo(xo[q][0]) - c0, b = bf_hi(xo[q][0]) - c0, c = bf_lo(xo[q][2]) - c0, d = bf_hi(xo[q][2]) - c0;
        s0 += (a + b) + (c + d); q0 += (a * a + b * b) + (c * c + d * d);
        a = bf_lo(xo[q][1]) - c1; b = bf_hi(xo[q][1]) - c1; c = bf_lo(xo[q][3]) - c1; d = bf_hi(xo[q][3]) - c1;
        s1 += (a + b) + (c + d); q1 += (a * a + b * b) + (c * c + d * d);
    }
    s0 += __shfl_xor_sync(~0u, s0, 1); s1 += __shfl_xor_sync(~0u, s1, 1); q0 += __shfl_xor_sync(~0u, q0, 1); q1 += __shfl_xor_sync(~0u, q1, 1);
    s0 += __shfl_xor_sync(~0u, s0, 2); s1 += __shfl_xor_sync(~0u, s1, 2); q0 += __shfl_xor_sync(~0u, q0, 2); q1 += __shfl_xor_sync(~0u, q1, 2);
    const float m0 = c0 + s0 * (1.f / 64.f), m1 = c1 + s1 * (1.f / 64.f);
    q0 = fmaxf(q0 - s0 * s0 * (1.f / 64.f), 0.f); q1 = fmaxf(q1 - s1 * s1 * (1.f / 64.f), 0.f);
    if ((lane & 3) == 0) stx(st_out + (lane >> 2), __float_as_uint(m0), __float_as_uint(q0), __float_as_uint(m1), __float_as_uint(q1), tag);
}

template <bool STATIC_ROLES>
__global__ void __launch_bounds__(NTHREADS, 1) fused_kernel(const __grid_constant__ Params P) {
    extern __shared__ __align__(1024) uint8_t smem[];
    const uint32_t sbase = smem_u32(smem);
    const uint32_t bar_full = sbase + SM_BAR, bar_empty = bar_full + NST * 8, bar_a = bar_empty + NST * 8, role_addr = bar_a + 32 * 8;
    const int tid = threadIdx.x, lane = tid & 31;
    const int warp = (int)uniform(tid >> 5);
    const uint32_t rank = cluster_rank();

    if (warp == 8) {
        if (elect_one()) {
            asm volatile("prefetch.tensormap [%0];" :: "l"(&P.tm_qkv) : "memory");
            if (sbase & 1023u) __trap();
            for (int s = 0; s < NST; s++) { mbar_init(bar_full + s * 8, 1); mbar_init(bar_empty + s * 8, 16); }
            asm volatile("fence.mbarrier_init.release.cluster;" ::: "memory");
        }
        __syncwarp();
    } else if (warp < 8) {
        if (elect_one()) {
            asm volatile("prefetch.tensormap [%0];" :: "l"(&P.tm_x) : "memory");
            for (int b = 0; b < 4; b++) mbar_init(bar_a + warp * 32 + b * 8, 1);
            asm volatile("fence.mbarrier_init.release.cluster;" ::: "memory");
        }
        __syncwarp();
    }
    int role = 0;
    if (STATIC_ROLES) {
        role = P.role_of_tpc[sm_id() >> 1];
    } else {
        if (tid == 32 && rank == 0) {
            const int gam = P.role_of_tpc[(sm_id() >> 1) % 72] & 7;
            unsigned long long old = atomicAdd(&g_ticket, 1ull << (8 * gam));
            int tk = (int)((old >> (8 * gam)) & 0xFF);
            int rl = gam * 8 + tk;
            if (tk >= 8) {
                unsigned long long cur; uint32_t n = 0;
                for (;;) {
                    asm volatile("ld.relaxed.gpu.global.u64 %0, [%1];" : "=l"(cur) : "l"(&g_ticket) : "memory");
                    int tot = 0;
                    for (int g = 0; g < 8; g++) tot += (int)((cur >> (8 * g)) & 0xFF);
                    if (tot >= NCLUSTERS) break;
                    spin_guard(n);
                }
                int orank = tk - 8;
                for (int g = 0; g < gam; g++) { int c = (int)((cur >> (8 * g)) & 0xFF); if (c > 8) orank += c - 8; }
                rl = -1;
                for (int g = 0; g < 8 && rl < 0; g++) {
                    int c = (int)((cur >> (8 * g)) & 0xFF);
                    int fr = c < 8 ? 8 - c : 0;
                    if (orank < fr) rl = g * 8 + c + orank; else orank -= fr;
                }
            }
            asm volatile("st.shared::cluster.u32 [%0], %1;" :: "r"(mapa(role_addr, 0)), "r"(rl) : "memory");
            asm volatile("st.shared::cluster.u32 [%0], %1;" :: "r"(mapa(role_addr, 1)), "r"(rl) : "memory");
        }
        __syncwarp();
        cluster_arrive();
        cluster_wait();
        asm volatile("ld.shared.u32 %0, [%1];" : "=r"(role) : "r"(role_addr) : "memory");
    }
    role = (int)__reduce_or_sync(~0u, (unsigned)role);
    if (STATIC_ROLES && role < 0) {
        if (tid == 0) {
            const unsigned e = ld_relaxed(&g_epoch[0]);
            uint32_t n = 0;
            for (int c = 0; c < NCLUSTERS; c++)
                while (ld_relaxed(&g_started[c * 8]) != e + 1) { __nanosleep(200); spin_guard(n); }
        }
        return;
    }
    const int grp = (role >> 3) * 2 + (int)rank;
    const int j = role & 7;

    if (warp >= 8) {
        asm volatile("setmaxnreg.dec.sync.aligned.u32 40;");
        unsigned epoch = 0;
        cluster_arrive(); cluster_wait();
        if (warp == 8) {
            if (elect_one()) {
                uint32_t s = 0, ph = 0;
                const uint32_t ring = opaque(sbase + SM_RING + rank * 8192u), fb = opaque(bar_full), eb = opaque(bar_empty);
                const int jj = (int)opaque((uint32_t)j), rk = (int)opaque(rank);
#define EMPTY_WAIT() mbar_wait(eb + s * 8, s >= XST ? ph : ph ^ 1)
#define STAGE_BEGIN() do { EMPTY_WAIT(); mbar_expect_tx(fb + s * 8, STAGE_BYTES); } while (0)
#define STAGE_END() do { if (++s == NST) { s = 0; ph ^= 1; } } while (0)
#pragma unroll 1
                for (int l = 0; l < 2; l++) {
#pragma unroll 1
                    for (int c = 0; c < 12; c++) {
                        const int cc = c >> 2;
                        const int col = (cc == 0 ? 512 : cc == 1 ? 1024 : 0) + 64 * jj;
                        STAGE_BEGIN();
                        tma2d_mc(ring + s * STAGE_BYTES, &P.tm_qkv, fb + s * 8, col, (c & 3) * 128 + rk * 64);
                        STAGE_END();
                    }
#pragma unroll 1
                    for (int q = 0; q < 4; q++) {
                        STAGE_BEGIN();
                        tma2d_mc(ring + s * STAGE_BYTES, &P.tm_wo, fb + s * 8, 64 * jj, q * 128 + rk * 64);
                        STAGE_END();
                    }
                    const CUtensorMap* tmu = rk == 0 ? &P.tm_wg : &P.tm_wu;
#pragma unroll 1
                    for (int c = 0; c < 28; c++) {
                        STAGE_BEGIN();
                        tma2d_mc(ring + s * STAGE_BYTES, tmu, fb + s * 8, 224 * jj + 32 * (c >> 2), (c & 3) * 128);
                        STAGE_END();
                    }
#pragma unroll 1
                    for (int q = 0; q < 14; q++) {
                        STAGE_BEGIN();
                        tma3d_mc(ring + s * STAGE_BYTES, &P.tm_wd, fb + s * 8, 128 * (jj >> 1) + 64 * rk, (jj & 1) * 224 + 32 * (q >> 1), 2 * (q & 1));
                        STAGE_END();
                    }
                }
            }
            __syncwarp();
        } else if (warp == 9) {
            if (lane == 0) {
                asm volatile("prefetch.tensormap [%0];" :: "l"(&P.tm_wo) : "memory");
                asm volatile("prefetch.tensormap [%0];" :: "l"(&P.tm_wg) : "memory");
                asm volatile("prefetch.tensormap [%0];" :: "l"(&P.tm_wu) : "memory");
                asm volatile("prefetch.tensormap [%0];" :: "l"(&P.tm_wd) : "memory");
            }
            epoch = ld_relaxed(&g_epoch[role * 8]);
            if (lane == 0 && rank == 0) asm volatile("st.relaxed.gpu.global.u32 [%0], %1;" :: "l"(&g_started[role * 8]), "r"(epoch + 1) : "memory");
        } else if (warp == 10) {
            mbar_wait(bar_full + 1 * 8, 0);
            const int cta = role * 2 + (int)rank;
            if (lane < 4) {
                const int m = lane + 1;
                const unsigned part = P.pf_bytes[m] / 128;
                asm volatile("cp.async.bulk.prefetch.L2.global [%0], %1;" :: "l"(P.pf_ptr[m] + (size_t)cta * part), "r"(part) : "memory");
            }
        }
        cluster_arrive();
        cluster_wait();
        if (tid == 288 && rank == 0) {
            asm volatile("st.relaxed.gpu.global.u32 [%0], %1;" :: "l"(&g_epoch[role * 8]), "r"(epoch + 1) : "memory");
            if (!STATIC_ROLES) {
                unsigned old = atomicAdd(&g_done, 1u);
                if (old == NCLUSTERS - 1) { g_ticket = 0ull; g_done = 0; }
            }
        }
    } else {
        asm volatile("setmaxnreg.inc.sync.aligned.u32 232;");
        const int wg = warp >> 2, w = warp & 3;
        const int t = (grp >> 3) * 16 + wg * 8 + (grp & 7);
        AStream as;
        as.slot0 = uniform(sbase + SM_STG + warp * (2 * ASLOT));
        as.bar0 = uniform(bar_a + warp * 32);
        as.ph = 0;
        const int xrow = t * 64 + w * 16;
        const uint32_t xhi = sbase + SM_RING + XST * STAGE_BYTES + warp * (2 * ASLOT);
        if (elect_one()) {
            mbar_expect_tx(as.bar0, 2 * ASLOT);
            tma3d(as.slot0, &P.tm_x, as.bar0, 0, xrow, 0);
            mbar_expect_tx(as.bar0 + 8, 2 * ASLOT);
            tma3d(xhi, &P.tm_x, as.bar0 + 8, 0, xrow, 4);
        }
        __syncwarp();
        cluster_arrive(); cluster_wait();
        uint32_t tagE = ld_relaxed(&g_epoch[role * 8]);
        Ring r;
        r.s = 0; r.ph = 0; r.rs = 0;
        r.desc0 = uniform((((sbase + SM_RING) & 0x3FFFFu) >> 4) | ((8192u >> 4) << 16));
        r.full0 = uniform(bar_full);
        r.empty_remote = mapa(bar_empty, lane & 1);
        r.rel_lane = lane < 2;
        const uint32_t u_tile = (uint32_t)((t * 4 + w) * 32 * 32);
        const uint32_t u_stoff = (uint32_t)((t * 4 + w) * 64);
        const uint32_t u_row = (uint32_t)(xrow * DM + 64 * j);
        const uint32_t u_kv = as.slot0 - w * (2 * ASLOT) + ASLOT;
        const uint32_t u_part = (uint32_t)((t * 4 + w) * 8 * 128);
        const uint32_t u_h = (uint32_t)((t * 4 + w) * 7 * 2 * 256);
#define LANE() opaque((uint32_t)lane)
#define ROWOFF(ln) (u_row + ((ln) >> 2) * DM + ((ln) & 3) * 2)

        const bool halo_warp = __reduce_or_sync(~0u, (unsigned)(w == 0 && t > 0)) != 0;
        const bool second_wg = __reduce_or_sync(~0u, (unsigned)wg) != 0;
        uint32_t a[32][4];
        float acc[32];
        float rstd0, rstd1;
        uint32_t res[4][4];
        {
            const uint32_t ln = LANE();
            const uint32_t lr = (ln & 7) + ((ln >> 3) & 1) * 8, hi = ln >> 4;
            const uint32_t lrB = (ln & 7) + (ln >> 4) * 8, hiB = (ln >> 3) & 1;
            uint32_t xzero = 0;
            float sm[2][4], d0[2][4], d1[2][4];
#pragma unroll
            for (int c = 0; c < 2; c++) {
#pragma unroll
                for (int e = 0; e < 4; e++) { sm[c][e] = 0.f; d0[c][e] = 0.f; d1[c][e] = 0.f; }
            }
            as.wait(0); as.wait(1);
            uint32_t pa[2][4], pb[2][4];
#pragma unroll
            for (int c = 0; c < 4; c++) {
                const uint32_t oa = lr * 128 + (((c * 2 + hi) ^ (lr & 7)) << 4), ob = lrB * 128 + (((c * 2 + hiB) ^ (lrB & 7)) << 4);
                pa[0][c] = as.slot0 + oa; pa[1][c] = xhi + oa; pb[0][c] = as.slot0 + ob; pb[1][c] = xhi + ob;
            }
            uint32_t dep = 0;
#pragma unroll
            for (int k = 0; k < 32; k++) {
                uint32_t b[4];
                ldsm4(a[k], pa[k >> 4][k & 3] + ((k >> 2) & 3) * 2048);
                ldsm4(b, pb[k >> 4][k & 3] + ((k >> 2) & 3) * 2048);
                mma16816(sm[k & 1], a[k][0], a[k][1], a[k][2], a[k][3], 0x3F803F80u, 0x3F803F80u);
                mma16816(d0[k & 1], a[k][0], a[k][1], a[k][2], a[k][3], b[0], b[1]);
                mma16816(d1[k & 1], a[k][0], a[k][1], a[k][2], a[k][3], b[2], b[3]);
            }
            {
                const uint32_t ro = (j & 3) * 2048 + (j < 4 ? 0u : xhi - as.slot0);
#pragma unroll
                for (int k = 0; k < 4; k++) { ldsm4(res[k], pa[0][k] + ro); dep |= res[k][1]; }
            }
            dep |= __float_as_uint(sm[0][0]) | __float_as_uint(sm[1][0]) | __float_as_uint(d1[0][3]) | __float_as_uint(d1[1][3]);
            asm volatile("{\n.reg .b32 t;\npopc.b32 t, %1;\nshr.u32 %0, t, 6;\n}" : "=r"(xzero) : "r"(dep));
            if (lane < 2) {
                const uint32_t eb = mapa(bar_empty + XST * 8 + xzero, lane & 1);
#pragma unroll
                for (int s = 0; s < 4; s++) mbar_arrive_cluster(eb + s * 8);
            }
            const float mean0 = (sm[0][0] + sm[1][0]) * (1.f / 512.f), mean1 = (sm[0][2] + sm[1][2]) * (1.f / 512.f);
            const uint32_t g = ln >> 2;
            float e0 = (g & 1) ? d0[0][1] + d0[1][1] : d0[0][0] + d0[1][0];
            float e1 = (g & 1) ? d1[0][3] + d1[1][3] : d1[0][2] + d1[1][2];
            const int src = g * 4 + (g >> 1);
            e0 = __shfl_sync(~0u, e0, src); e1 = __shfl_sync(~0u, e1, src);
            rstd0 = rsqrtf(fmaxf(e0 * (1.f / 512.f) - mean0 * mean0, 0.f) + 1e-5f);
            rstd1 = rsqrtf(fmaxf(e1 * (1.f / 512.f) - mean1 * mean1, 0.f) + 1e-5f);
            center(a, mean0, mean1);
            tagE = uniform((tagE + 1) & 1);
        }

        auto group = [&](float (&d)[32], const uint32_t (*af)[4], auto first, auto nk, uint32_t dhi, uint32_t kstep) {
            mbar_wait(r.full0 + r.s * 8, r.ph);
            const uint32_t dlo = r.desc0 + r.s * (STAGE_BYTES >> 4);
            wgmma_fence();
            wgmma_n64<!decltype(first)::value>(d, af[0], dlo, dhi);
#pragma unroll
            for (int k = 1; k < decltype(nk)::value; k++) wgmma_n64<true>(d, af[k], dlo + k * kstep, dhi);
            wgmma_commit();
            r.advance();
        };
        using T_ = BoolC<true>; using F_ = BoolC<false>; using K8 = IntC<8>; using K7 = IntC<7>;
        constexpr uint32_t DHI128 = (1024u >> 4) | (1u << 30), DHI64 = (512u >> 4) | (2u << 30);
        auto h_epilogue = [&](int c, uint32_t tag) {
            const float q0 = rstd0 * rstd0, q1 = rstd1 * rstd1;
            uint4* hg = g_x + (X_H + u_h + (c * 2 + (j & 1)) * 256 + (j >> 1) * 64 + LANE());
#pragma unroll
            for (int ks = 0; ks < 2; ks++) {
                const int b = ks * 8;
                stx(hg + ks * 32,
                    pack2(acc[b] * acc[16 + b] * q0, acc[b + 1] * acc[17 + b] * q0),
                    pack2(acc[b + 2] * acc[18 + b] * q1, acc[b + 3] * acc[19 + b] * q1),
                    pack2(acc[b + 4] * acc[20 + b] * q0, acc[b + 5] * acc[21 + b] * q0),
                    pack2(acc[b + 6] * acc[22 + b] * q1, acc[b + 7] * acc[23 + b] * q1), tag);
            }
        };
        auto residual = [&](bool wo, uint32_t tag, uint32_t vbit, bool last) {
            const uint32_t ln = LANE();
#pragma unroll
            for (int q = 0; q < 4; q++) {
                res[q][0] = pack2(acc[8 * q] + bf_lo(res[q][0]), acc[8 * q + 1] + bf_hi(res[q][0]));
                res[q][1] = pack2(acc[8 * q + 2] + bf_lo(res[q][1]), acc[8 * q + 3] + bf_hi(res[q][1]));
                res[q][2] = pack2(acc[8 * q + 4] + bf_lo(res[q][2]), acc[8 * q + 5] + bf_hi(res[q][2]));
                res[q][3] = pack2(acc[8 * q + 6] + bf_lo(res[q][3]), acc[8 * q + 7] + bf_hi(res[q][3]));
            }
            if (!last) {
                publish_x(res, g_x + ((wo ? X_X1 : X_X2) + u_tile + 4 * j * 32 + ln), g_x + ((wo ? X_ST1 : X_ST2) + u_stoff + j * 8), (int)ln, tag, vbit);
            } else {
                const uint32_t srow = (ln & 7) + ((ln >> 3) & 1) * 8;
#pragma unroll
                for (int q = 0; q < 4; q++)
                    asm volatile("stmatrix.sync.aligned.m8n8.x4.shared.b16 [%0], {%1,%2,%3,%4};"
                                 :: "r"(as.slot0 + srow * 128 + (((2 * q + (ln >> 4)) ^ (srow & 7)) << 4)),
                                    "r"(res[q][0]), "r"(res[q][1]), "r"(res[q][2]), "r"(res[q][3]) : "memory");
                __syncwarp();
                uint4* o = (uint4*)(P.out + u_row) + (ln & 7);
#pragma unroll
                for (int q = 0; q < 4; q++) {
                    const uint32_t row = q * 4 + (ln >> 3);
                    uint32_t v[4];
                    lds128(v, as.slot0 + row * 128 + (((ln & 7) ^ (row & 7)) << 4));
                    asm volatile("st.global.v4.u32 [%0], {%1,%2,%3,%4};" :: "l"(o + row * (DM / 8)), "r"(v[0]), "r"(v[1]), "r"(v[2]), "r"(v[3]) : "memory");
                }
            }
        };

#pragma unroll 1
        for (int l = 0; l < 2; l++) {
            const uint32_t tagL = (uint32_t)(l ^ 1);
#pragma unroll 1
            for (int st = 0; st < 5; st++) {
                const bool fetch = (st == 0 && l == 1) || st >= 3;
                uint32_t src = 0;
                uint32_t tag = tagL, keep = ~0u, m0 = 0u, m1 = 0u;
                if (fetch) {
                    const uint32_t ln = LANE();
                    if (st == 3) {
                        src = X_O + u_tile;
                        named_bar_sync(1 + wg, 128);
                        delay_cycles(DELAY_O);
                        as.issue(0, src, true); as.issue(1, src + 256, true);
                    } else {
                        const bool x2 = st == 0;
                        src = (x2 ? X_X2 : X_X1) + u_tile;
                        if (x2) { tag = tagE; keep = ~1u; }
                        delay_cycles(DELAY_X);
                        float mean0, mean1;
                        as.issue(0, src, true); as.issue(1, src + 256, true);
                        fetch_stats(g_x + ((x2 ? X_ST2 : X_ST1) + u_stoff), tag, ln, keep, mean0, mean1, rstd0, rstd1);
                        m0 = pack2(mean0, mean0); m1 = pack2(mean1, mean1);
                    }
                }
                {
                    const uint32_t dhi = st == 4 ? DHI64 : DHI128, kstep = st == 4 ? 64u : 128u;
                    const uint32_t ln = LANE();
#pragma unroll
                    for (int q = 0; q < 4; q++) {
                        if ((q & 1) == 0 && fetch) {
                            const uint32_t p = as.slot0 + ln * 16;
                            uint32_t n = 0;
                            for (;;) {
                                as.wait(0); as.wait(1);
#pragma unroll
                                for (int k = 0; k < 16; k++) lds128_re(a[8 * q + k], p + k * 512);
                                uint32_t bad = 0;
#pragma unroll
                                for (int k = 0; k < 16; k++) bad |= a[8 * q + k][0] ^ tag;
                                if (__reduce_or_sync(~0u, bad & 1) == 0) break;
                                spin_guard(n);
                                as.issue(0, src + q * 256, true); as.issue(1, src + q * 256 + 256, true);
                            }
                        }
                        if (fetch && st != 3) {
#pragma unroll
                            for (int k = 8 * q; k < 8 * q + 8; k++) {
                                a[k][0] = hsub2(a[k][0] & keep, m0); a[k][1] = hsub2(a[k][1], m1);
                                a[k][2] = hsub2(a[k][2], m0); a[k][3] = hsub2(a[k][3], m1);
                            }
                        }
                        if (q == 0 && st <= 2 && (second_wg || l > 0 || st > 0)) named_bar_sync(second_wg ? 6 : 5, 256);
                        if (q == 0) group(acc, &a[0], T_{}, K8{}, dhi, kstep); else group(acc, &a[8 * q], F_{}, K8{}, dhi, kstep);
                        if (q == 0) { as.issue(0, src + 512, fetch); as.issue(1, src + 768, fetch); }
                        if (q == 3 && st <= 2) named_bar_arrive(second_wg ? 5 : 6, 256);
                        if (q > 0) { wgmma_wait<1>(); r.release(); }
                    }
                }
                const uint32_t halo_in = X_HALO + (uint32_t)(((l * NT + t - 1) * 8 + j) * 256);
                const bool use_halo = st == 2 && halo_warp;
                as.issue(0, halo_in, use_halo);
                wgmma_wait<0>(); r.release();
                fence_acc(acc);
                if (st == 4) {
                    h_epilogue(0, tagL);
                } else if (st == 3) {
                    residual(true, tagL, tagL, false);
                } else {
                    const uint32_t ln = LANE();
                    uint32_t f[4][4];
#pragma unroll
                    for (int h = 0; h < 4; h++) {
                        f[h][0] = pack2(acc[8 * h] * rstd0, acc[8 * h + 1] * rstd0); f[h][1] = pack2(acc[8 * h + 2] * rstd1, acc[8 * h + 3] * rstd1);
                        f[h][2] = pack2(acc[8 * h + 4] * rstd0, acc[8 * h + 5] * rstd0); f[h][3] = pack2(acc[8 * h + 6] * rstd1, acc[8 * h + 7] * rstd1);
                    }
                    const uint32_t kv_own = u_kv + w * (2 * ASLOT) + ln * 16;
                    if (st < 2) {
                        uint4* halo_out = g_x + (X_HALO + (uint32_t)(((l * NT + t) * 8 + j) * 256 + st * 128) + ln);
#pragma unroll
                        for (int h = 0; h < 4; h++) {
                            if (st == 1) { f[h][0] = movmat(f[h][0]); f[h][1] = movmat(f[h][1]); f[h][2] = movmat(f[h][2]); f[h][3] = movmat(f[h][3]); }
                            sts128(kv_own + st * 2048 + h * 512, f[h][0], f[h][1], f[h][2], f[h][3]);
                            if (w == 3) stx(halo_out + h * 32, f[h][0], f[h][1], f[h][2], f[h][3], tagE);
                        }
                    } else {
                        if (use_halo) as.validate(0, halo_in, tagE, ln);
                        named_bar_sync(1 + wg, 128);
                        const uint32_t kv_prev = w > 0 ? kv_own - 2 * ASLOT : as.slot0 + ln * 16;
                        const uint32_t keep_prev = w > 0 ? ~0u : ~1u;
                        const bool has_prev = (w > 0) || (t > 0);
                        const uint32_t any_prev = has_prev ? ~0u : 0u;
                        const bool hi_t = (ln & 3) > (ln >> 3);
                        const bool odd = (ln >> 2) & 1;
                        constexpr float SC = 0.25f * 1.4426950408889634f;
                        const float NEG = __int_as_float(0xff800000);
                        const uint32_t sh16 = odd ? 16 : 0;
                        uint4* odst = g_x + (X_O + u_tile + 4 * j * 32 + ln);
                        uint32_t kp[4][4], ko[4][4], vp[4][4], vo[4][4];
#pragma unroll
                        for (int h = 0; h < 4; h++) { lds128(kp[h], kv_prev + h * 512); lds128(ko[h], kv_own + h * 512); }
#pragma unroll
                        for (int h = 0; h < 4; h++) { lds128(vp[h], kv_prev + 2048 + h * 512); lds128(vo[h], kv_own + 2048 + h * 512); }
                        float eg[4], cg[4], eh[4], ch[4];
#pragma unroll
                        for (int h = 0; h < 4; h++) {
                            kp[h][0] &= keep_prev;
                            float s0[4] = {0, 0, 0, 0}, s1[4] = {0, 0, 0, 0}, s2[4] = {0, 0, 0, 0}, s3[4] = {0, 0, 0, 0};
                            mma16816(s0, f[h][0], f[h][1], f[h][2], f[h][3], kp[h][0], kp[h][2]);
                            mma16816(s1, f[h][0], f[h][1], f[h][2], f[h][3], kp[h][1], kp[h][3]);
                            mma16816(s2, f[h][0], f[h][1], f[h][2], f[h][3], ko[h][0], ko[h][2]);
                            mma16816(s3, f[h][0], f[h][1], f[h][2], f[h][3], ko[h][1], ko[h][3]);
                            float t0g = odd ? s0[1] : s0[0], t1g = odd ? s1[1] : s1[0], t2g = odd ? s2[1] : s2[0];
                            float t1h = odd ? s1[3] : s1[2], t2h = odd ? s2[3] : s2[2], t3h = odd ? s3[3] : s3[2];
                            if (!has_prev) { t0g = NEG; t1g = NEG; t1h = NEG; }
                            eg[h] = hi_t ? t0g : t2g; cg[h] = t1g;
                            eh[h] = hi_t ? t1h : t3h; ch[h] = t2h;
                        }
                        float mg[4], mh[4];
#pragma unroll
                        for (int h = 0; h < 4; h++) { mg[h] = fmaxf(eg[h], cg[h]); mh[h] = fmaxf(eh[h], ch[h]); }
#pragma unroll
                        for (int h = 0; h < 4; h++) { mg[h] = fmaxf(mg[h], __shfl_xor_sync(~0u, mg[h], 1)); mh[h] = fmaxf(mh[h], __shfl_xor_sync(~0u, mh[h], 1)); }
#pragma unroll
                        for (int h = 0; h < 4; h++) { mg[h] = fmaxf(mg[h], __shfl_xor_sync(~0u, mg[h], 2)); mh[h] = fmaxf(mh[h], __shfl_xor_sync(~0u, mh[h], 2)); }
                        float sg[4], sh[4];
#pragma unroll
                        for (int h = 0; h < 4; h++) {
                            eg[h] = ex2((eg[h] - mg[h]) * SC); cg[h] = ex2((cg[h] - mg[h]) * SC);
                            eh[h] = ex2((eh[h] - mh[h]) * SC); ch[h] = ex2((ch[h] - mh[h]) * SC);
                            sg[h] = eg[h] + cg[h]; sh[h] = eh[h] + ch[h];
                        }
#pragma unroll
                        for (int h = 0; h < 4; h++) { sg[h] += __shfl_xor_sync(~0u, sg[h], 1); sh[h] += __shfl_xor_sync(~0u, sh[h], 1); }
#pragma unroll
                        for (int h = 0; h < 4; h++) { sg[h] += __shfl_xor_sync(~0u, sg[h], 2); sh[h] += __shfl_xor_sync(~0u, sh[h], 2); }
#pragma unroll
                        for (int h = 0; h < 4; h++) {
                            const float ig = __fdividef(1.f, sg[h]), ih = __fdividef(1.f, sh[h]);
                            const uint32_t beg = pack2(eg[h] * ig, 0.f) << sh16, b1g = pack2(cg[h] * ig, 0.f) << sh16;
                            const uint32_t beh = pack2(eh[h] * ih, 0.f) << sh16, b2h = pack2(ch[h] * ih, 0.f) << sh16;
                            const uint32_t pa0 = hi_t ? beg : 0u, pa3 = hi_t ? beh : 0u;
                            const uint32_t pb0 = hi_t ? 0u : beg, pb3 = hi_t ? 0u : beh;
                            float o0[4] = {0, 0, 0, 0}, o1[4] = {0, 0, 0, 0};
                            mma16816(o0, pa0, 0u, b1g, pa3, vp[h][0] & keep_prev & any_prev, vp[h][1] & any_prev);
                            mma16816(o1, pa0, 0u, b1g, pa3, vp[h][2] & any_prev, vp[h][3] & any_prev);
                            mma16816(o0, pb0, b2h, 0u, pb3, vo[h][0], vo[h][1]);
                            mma16816(o1, pb0, b2h, 0u, pb3, vo[h][2], vo[h][3]);
                            stx(odst + h * 32, pack2(o0[0], o0[1]), pack2(o0[2], o0[3]), pack2(o1[0], o1[1]), pack2(o1[2], o1[3]), tagL);
                        }
                    }
                }
            }
            const uint32_t h_in = X_H + u_h + (j & 1) * 256;
#pragma unroll 1
            for (int c = 1; c < 7; c++) {
                named_bar_sync(second_wg ? 6 : 5, 256);
                group(acc, &a[0], T_{}, K8{}, DHI64, 64u);
                group(acc, &a[8], F_{}, K8{}, DHI64, 64u);
                wgmma_wait<1>(); r.release();
                group(acc, &a[16], F_{}, K8{}, DHI64, 64u);
                wgmma_wait<1>(); r.release();
                group(acc, &a[24], F_{}, K8{}, DHI64, 64u);
                if (!second_wg || c < 6 || l == 0) named_bar_arrive(second_wg ? 5 : 6, 256);
                wgmma_wait<1>(); r.release();
                wgmma_wait<0>(); r.release();
                fence_acc(acc);
                if (c == 5) { as.issue(0, h_in, true); as.issue(1, h_in + 512, true); }
                h_epilogue(c, tagL);
            }
            {
                const uint32_t ln = LANE();
                const uint32_t p = as.slot0 + ln * 16;
#pragma unroll
                for (int k = 16; k < 32; k++) { a[k][0] = 0u; a[k][1] = 0u; a[k][2] = 0u; a[k][3] = 0u; }
                float accD[64];
                constexpr uint32_t DHI = DHI128;
                auto piece = [&](int c, auto bsel, auto first) {
                    constexpr int B = decltype(bsel)::value * 8;
                    const uint32_t sl = decltype(bsel)::value;
                    uint32_t n = 0;
                    for (;;) {
                        as.wait(sl);
#pragma unroll
                        for (int k = 0; k < 8; k++) lds128_re(a[B + k], p + sl * ASLOT + k * 512);
                        uint32_t bad = 0;
#pragma unroll
                        for (int k = 0; k < 8; k++) bad |= a[B + k][0] ^ tagL;
                        if (__reduce_or_sync(~0u, bad & 1) == 0) break;
                        spin_guard(n);
                        as.issue(sl, h_in + c * 512, true);
                    }
                    as.issue(sl, h_in + (c + 2) * 512, c + 2 < 7);
#pragma unroll
                    for (int hb = 0; hb < 2; hb++) {
                        mbar_wait(r.full0 + r.s * 8, r.ph);
                        const uint32_t dlo = r.desc0 + r.s * (STAGE_BYTES >> 4);
                        wgmma_fence();
                        if (decltype(first)::value && hb == 0) wgmma_n128<false>(accD, a[B], dlo, DHI); else wgmma_n128<true>(accD, a[B + 4 * hb], dlo, DHI);
#pragma unroll
                        for (int k = 1; k < 4; k++) wgmma_n128<true>(accD, a[B + 4 * hb + k], dlo + k * 128, DHI);
                        wgmma_commit();
                        r.advance();
                        if (!(decltype(first)::value && hb == 0)) { wgmma_wait<1>(); r.release(); }
                    }
                };
                piece(0, IntC<0>{}, T_{});
#pragma unroll 1
                for (int c = 1; c < 7; c += 2) {
                    piece(c, IntC<1>{}, F_{});
                    piece(c + 1, IntC<0>{}, F_{});
                }
                wgmma_wait<0>(); r.release();
                fence_acc64(accD);
                const bool odd_j = j & 1;
                {
                    uint4* q_ = g_x + (X_P + u_part + (j ^ 1) * 128 + ln);
#pragma unroll
                    for (int q = 0; q < 4; q++) {
                        float o[8];
#pragma unroll
                        for (int e = 0; e < 8; e++) { o[e] = odd_j ? accD[8 * q + e] : accD[32 + 8 * q + e]; acc[8 * q + e] = odd_j ? accD[32 + 8 * q + e] : accD[8 * q + e]; }
                        stx(q_ + q * 32, pack2(o[0], o[1]), pack2(o[2], o[3]), pack2(o[4], o[5]), pack2(o[6], o[7]), tagL);
                    }
                }
                const uint32_t part_in = X_P + u_part + j * 128;
                probe(g_x + (part_in + 96 + (ln & 7)), tagL);
                as.issue_q(0, part_in, true);
                {
                    const uint32_t idm = (ln >> 3) == (ln & 3) ? (((ln >> 2) & 1) ? 0x3F800000u : 0x00003F80u) : 0u;
                    uint32_t v[4][4], n = 0;
                    for (;;) {
                        as.wait(0);
#pragma unroll
                        for (int k = 0; k < 4; k++) lds128(v[k], p + k * 512);
                        if (__reduce_or_sync(~0u, ((v[0][0] ^ tagL) | (v[1][0] ^ tagL) | (v[2][0] ^ tagL) | (v[3][0] ^ tagL)) & 1) == 0) break;
                        spin_guard(n);
                        as.issue_q(0, part_in, true);
                    }
#pragma unroll
                    for (int k = 0; k < 4; k++) {
                        float lo[4] = {acc[8 * k], acc[8 * k + 1], acc[8 * k + 2], acc[8 * k + 3]}, hi[4] = {acc[8 * k + 4], acc[8 * k + 5], acc[8 * k + 6], acc[8 * k + 7]};
                        mma16816(lo, v[k][0], v[k][1], v[k][2], v[k][3], idm, 0u);
                        mma16816(hi, v[k][0], v[k][1], v[k][2], v[k][3], 0u, idm);
                        acc[8 * k] = lo[0]; acc[8 * k + 1] = lo[1]; acc[8 * k + 2] = lo[2]; acc[8 * k + 3] = lo[3];
                        acc[8 * k + 4] = hi[0]; acc[8 * k + 5] = hi[1]; acc[8 * k + 6] = hi[2]; acc[8 * k + 7] = hi[3];
                    }
                }
                residual(false, tagE, 0u, l == 1);
            }
        }
        cluster_arrive();
        cluster_wait();
    }
}

typedef CUresult (*EncodeFn)(CUtensorMap*, CUtensorMapDataType, cuuint32_t, void*, const cuuint64_t*, const cuuint64_t*,
                             const cuuint32_t*, const cuuint32_t*, CUtensorMapInterleave, CUtensorMapSwizzle,
                             CUtensorMapL2promotion, CUtensorMapFloatOOBfill);

void encode_2d(EncodeFn enc, CUtensorMap* tm, const void* ptr, uint64_t cols, uint64_t rows, uint32_t box_c, uint32_t box_r, CUtensorMapSwizzle sw) {
    cuuint64_t dims[2] = {cols, rows};
    cuuint64_t strides[1] = {cols * 2};
    cuuint32_t box[2] = {box_c, box_r};
    cuuint32_t es[2] = {1, 1};
    enc(tm, CU_TENSOR_MAP_DATA_TYPE_BFLOAT16, 2, const_cast<void*>(ptr), dims, strides, box, es, CU_TENSOR_MAP_INTERLEAVE_NONE, sw,
        CU_TENSOR_MAP_L2_PROMOTION_L2_128B, CU_TENSOR_MAP_FLOAT_OOB_FILL_NONE);
}

void build_role_table(Params& P) {
    int M[10] = {0};
    bool ok = true;
    for (int c = 1; c <= 8 && ok; c++) {
        cudaLaunchConfig_t cfg = {};
        cfg.gridDim = dim3(2 * c); cfg.blockDim = dim3(NTHREADS); cfg.dynamicSmemBytes = SM_TOTAL;
        cudaLaunchAttribute at[1];
        at[0].id = cudaLaunchAttributeClusterDimension; at[0].val.clusterDim.x = 2 * c; at[0].val.clusterDim.y = 1; at[0].val.clusterDim.z = 1;
        cfg.attrs = at; cfg.numAttrs = 1;
        if (cudaOccupancyMaxActiveClusters(&M[c], fused_kernel<true>, &cfg) != cudaSuccess) { ok = false; (void)cudaGetLastError(); }
    }
    int n[10] = {0};
    bool found = false;
    if (ok) {
        for (int n9 = 0; n9 <= 8 && !found; n9++) for (int n8 = 0; n8 + n9 <= 8 && !found; n8++)
        for (int n7 = 0; n7 + n8 + n9 <= 8 && !found; n7++) for (int n6 = 0; n6 + n7 + n8 + n9 <= 8 && !found; n6++)
        for (int n5 = 0; n5 + n6 + n7 + n8 + n9 <= 8 && !found; n5++) for (int n4 = 0; n4 + n5 + n6 + n7 + n8 + n9 <= 8 && !found; n4++)
        for (int n3 = 0; n3 + n4 + n5 + n6 + n7 + n8 + n9 <= 8 && !found; n3++)
        for (int n2 = 0; n2 + n3 + n4 + n5 + n6 + n7 + n8 + n9 <= 8 && !found; n2++) {
            int cnt[10] = {0, 0, n2, n3, n4, n5, n6, n7, n8, n9};
            int tot = 0; for (int T = 2; T <= 9; T++) tot += T * cnt[T];
            cnt[1] = M[1] - tot;
            if (cnt[1] < 0) continue;
            bool match = true;
            for (int c = 2; c <= 8 && match; c++) { int m = 0; for (int T = 1; T <= 9; T++) m += cnt[T] * (T / c); match = (m == M[c]); }
            if (match) { for (int T = 1; T <= 9; T++) n[T] = cnt[T]; found = true; }
        }
    }
    int gpc[72];
    for (int i = 0; i < 72; i++) gpc[i] = i & 7;
    if (found) {
        int size[8], ng = 0;
        for (int T = 2; T <= 9; T++) for (int k = 0; k < n[T] && ng < 8; k++) size[ng++] = T;
        int id = 0, fill[8] = {0};
        for (int rnd = 0; rnd < 9; rnd++) for (int gI = 0; gI < ng; gI++) if (size[gI] > rnd && id < 72) { gpc[id++] = gI; fill[gI]++; }
        for (int k = 0; k < n[1] && id < 72; k++) {
            int best = 0; for (int gI = 1; gI < 8; gI++) if (fill[gI] < fill[best]) best = gI;
            gpc[id++] = best; fill[best]++;
        }
    }
    int dev = 0, sms = 0;
    cudaGetDevice(&dev);
    cudaDeviceGetAttribute(&sms, cudaDevAttrMultiProcessorCount, dev);
    P.static_roles = (ok && sms == 132 && M[1] == 66) ? 1 : 0;
    if (!P.static_roles) { for (int i = 0; i < 72; i++) P.role_of_tpc[i] = (signed char)gpc[i]; return; }
    int cnt[8] = {0};
    bool used[64] = {false};
    for (int i = 0; i < 72; i++) P.role_of_tpc[i] = -1;
    int pending[72], np = 0;
    for (int i = 0; i < 66; i++) { int gI = gpc[i] & 7; if (cnt[gI] < 8) { int rl = gI * 8 + cnt[gI]++; P.role_of_tpc[i] = (signed char)rl; used[rl] = true; } else pending[np++] = i; }
    int nx = 0;
    for (int k = 0; k < np; k++) { while (nx < 64 && used[nx]) nx++; if (nx < 64) { P.role_of_tpc[pending[k]] = (signed char)nx; used[nx] = true; } }
}

}

extern "C" void kernel_launch(void* const* d_in, const int* in_sizes, int n_in, void* d_out, int out_size) {
    (void)in_sizes; (void)n_in; (void)out_size;
    static Params P;
    static bool init = false;
    static const void* cached[8] = {nullptr};
    bool same = init;
    for (int i = 0; i < 7 && same; i++) same = (cached[i] == d_in[i]);
    same = same && cached[7] == d_out;
    if (!same) {
        void* fn = nullptr;
        cudaDriverEntryPointQueryResult st;
        cudaGetDriverEntryPoint("cuTensorMapEncodeTiled", &fn, cudaEnableDefault, &st);
        EncodeFn enc = (EncodeFn)fn;
        const void* wqkv = d_in[1]; const void* wo = d_in[2];
        const void* wg = d_in[4]; const void* wu = d_in[5]; const void* wd = d_in[6];
        {
            cuuint64_t dims[3] = {64, 2048, 8};
            cuuint64_t strides[2] = {1024, 128};
            cuuint32_t box[3] = {64, 16, 4};
            cuuint32_t es[3] = {1, 1, 1};
            enc(&P.tm_x, CU_TENSOR_MAP_DATA_TYPE_BFLOAT16, 3, d_in[0], dims, strides, box, es, CU_TENSOR_MAP_INTERLEAVE_NONE,
                CU_TENSOR_MAP_SWIZZLE_128B, CU_TENSOR_MAP_L2_PROMOTION_L2_128B, CU_TENSOR_MAP_FLOAT_OOB_FILL_NONE);
        }
        encode_2d(enc, &P.tm_qkv, wqkv, 1536, 512, 64, 64, CU_TENSOR_MAP_SWIZZLE_128B);
        encode_2d(enc, &P.tm_wo, wo, 512, 512, 64, 64, CU_TENSOR_MAP_SWIZZLE_128B);
        encode_2d(enc, &P.tm_wg, wg, 1792, 512, 32, 128, CU_TENSOR_MAP_SWIZZLE_64B);
        encode_2d(enc, &P.tm_wu, wu, 1792, 512, 32, 128, CU_TENSOR_MAP_SWIZZLE_64B);
        {
            cuuint64_t dims[3] = {512, 448, 4};
            cuuint64_t strides[2] = {1024, 448 * 1024};
            cuuint32_t box[3] = {64, 32, 2};
            cuuint32_t es[3] = {1, 1, 1};
            enc(&P.tm_wd, CU_TENSOR_MAP_DATA_TYPE_BFLOAT16, 3, const_cast<void*>(wd), dims, strides, box, es, CU_TENSOR_MAP_INTERLEAVE_NONE,
                CU_TENSOR_MAP_SWIZZLE_128B, CU_TENSOR_MAP_L2_PROMOTION_L2_128B, CU_TENSOR_MAP_FLOAT_OOB_FILL_NONE);
        }
        P.x = (const __nv_bfloat16*)d_in[0];
        P.out = (__nv_bfloat16*)d_out;
        P.pf_ptr[0] = (const uint8_t*)wqkv; P.pf_bytes[0] = 512 * 1536 * 2;
        P.pf_ptr[1] = (const uint8_t*)wo; P.pf_bytes[1] = 512 * 512 * 2;
        P.pf_ptr[2] = (const uint8_t*)wg; P.pf_bytes[2] = 512 * 1792 * 2;
        P.pf_ptr[3] = (const uint8_t*)wu; P.pf_bytes[3] = 512 * 1792 * 2;
        P.pf_ptr[4] = (const uint8_t*)wd; P.pf_bytes[4] = 512 * 1792 * 2;
        if (!init) {
            cudaFuncSetAttribute(fused_kernel<true>, cudaFuncAttributeMaxDynamicSharedMemorySize, SM_TOTAL);
            cudaFuncSetAttribute(fused_kernel<true>, cudaFuncAttributeNonPortableClusterSizeAllowed, 1);
            cudaFuncSetAttribute(fused_kernel<false>, cudaFuncAttributeMaxDynamicSharedMemorySize, SM_TOTAL);
            build_role_table(P);
        }
        for (int i = 0; i < 7; i++) cached[i] = d_in[i];
        cached[7] = d_out;
        init = true;
    }
    cudaLaunchConfig_t cfg = {};
    cfg.gridDim = dim3(P.static_roles ? 132 : 2 * NCLUSTERS); cfg.blockDim = dim3(NTHREADS); cfg.dynamicSmemBytes = SM_TOTAL;
    cfg.stream = cudaStreamPerThread;
    cudaLaunchAttribute at[1];
    at[0].id = cudaLaunchAttributeClusterDimension; at[0].val.clusterDim.x = 2; at[0].val.clusterDim.y = 1; at[0].val.clusterDim.z = 1;
    cfg.attrs = at; cfg.numAttrs = 1;
    if (P.static_roles) cudaLaunchKernelEx(&cfg, fused_kernel<true>, P);
    else cudaLaunchKernelEx(&cfg, fused_kernel<false>, P);
}
```
